```python
import torch

def _softmax(x, axis=-1):
    return torch.softmax(x, dim=axis)
def _gelu(x):
    return torch.nn.functional.gelu(x, approximate="tanh")
def _silu(x):
    return torch.nn.functional.silu(x)
def _sigmoid(x):
    return torch.sigmoid(x)
def _layernorm(x, axis=-1, eps=1e-5):
    m = x.mean(dim=axis, keepdim=True)
    v = x.var(dim=axis, keepdim=True, unbiased=False)
    return (x - m) / torch.sqrt(v + eps)
def _scatter_add(tgt, idx, src, axis=0):
    return tgt.clone().index_add_(axis, idx, src)
def _segment_sum(src, seg, n):
    out = torch.zeros((n,) + src.shape[1:], dtype=src.dtype)
    return out.index_add_(0, seg, src)
def _pad(x, pw):
    flat = tuple(v for pair in reversed(pw) for v in pair)
    return torch.nn.functional.pad(x, flat)

kernel_name = 'concat_heads__gqa_block_cached__sliding_block_cached__decode'

def setup_inputs():

    _w = (lambda a: (lambda t: t.to(torch.bfloat16) if t.is_floating_point() else t)(torch.as_tensor(a)))
    def _A_setup():
        B, Sq, D = 2, 1, 448
        Hq, Hkv, Sk, Dh = 16, 8, 8192, 256
        assert Hq % Hkv == 0, (Hq, Hkv)
        return {
            "x": _w((lambda *s: torch.randn(*s, dtype=torch.bfloat16) * 0.8)(B, Sq, D)),
            "k_cache": _w((lambda *s: torch.randn(*s, dtype=torch.bfloat16) * 1.6)(B, Hkv, Sk, Dh)),
            "v_cache": _w((lambda *s: torch.randn(*s, dtype=torch.bfloat16) * 0.2)(B, Hkv, Sk, Dh)),
            "wq": _w((lambda *s: torch.randn(*s, dtype=torch.bfloat16) * 1.6)(D, Hq * Dh) * (D ** -0.5)),
            "wo": _w((lambda *s: torch.randn(*s, dtype=torch.bfloat16) * 0.2)(Hq * Dh, D) * ((Hq * Dh) ** -0.5)),
        }
    _A_in = _A_setup()

    def _B_setup():
        B, Sq, D = 2, 1, 448
        Hq, Hkv, Sk, Dh = 16, 8, 8192, 256
        assert Hq % Hkv == 0, (Hq, Hkv)
        return {
            "x": _w((lambda *s: torch.randn(*s, dtype=torch.bfloat16) * 0.8)(B, Sq, D)),
            "k_cache": _w((lambda *s: torch.randn(*s, dtype=torch.bfloat16) * 1.6)(B, Hkv, Sk, Dh)),
            "v_cache": _w((lambda *s: torch.randn(*s, dtype=torch.bfloat16) * 0.2)(B, Hkv, Sk, Dh)),
            "wq": _w((lambda *s: torch.randn(*s, dtype=torch.bfloat16) * 1.6)(D, Hq * Dh) * (D ** -0.5)),
            "wo": _w((lambda *s: torch.randn(*s, dtype=torch.bfloat16) * 0.2)(Hq * Dh, D) * ((Hq * Dh) ** -0.5)),
        }
    _B_in = _B_setup()

    return {
        "A_x": _A_in["x"],
        "A_k_cache": _A_in["k_cache"],
        "A_v_cache": _A_in["v_cache"],
        "A_wq": _A_in["wq"],
        "A_wo": _A_in["wo"],
        "B_x": _B_in["x"],
        "B_k_cache": _B_in["k_cache"],
        "B_v_cache": _B_in["v_cache"],
        "B_wq": _B_in["wq"],
        "B_wo": _B_in["wo"],
    }

def reference(A_x, A_k_cache, A_v_cache, A_wq, A_wo, B_x, B_k_cache, B_v_cache, B_wq, B_wo):
    def _A_ref(x, k_cache, v_cache, wq, wo):
        B, Sq, D = x.shape
        Hq, Dh = 16, 256
        Hkv = k_cache.shape[1]
        rep = Hq // Hkv
        q = (lambda x, *d: x.permute(*d))((x @ wq).reshape(B, Sq, Hq, Dh), 0, 2, 1, 3)
        k = (lambda x, n, axis: torch.repeat_interleave(x, n, dim=axis))(k_cache, rep, axis=1)
        v = (lambda x, n, axis: torch.repeat_interleave(x, n, dim=axis))(v_cache, rep, axis=1)
        scores = torch.einsum("bhqd,bhkd->bhqk", q, k) * (Dh ** -0.5)
        p = _softmax(scores, axis=-1)
        o = torch.einsum("bhqk,bhkd->bhqd", p, v)
        return (lambda x, *d: x.permute(*d))(o, 0, 2, 1, 3).reshape(B, Sq, Hq * Dh) @ wo

    def _B_ref(x, k_cache, v_cache, wq, wo):
        B, Sq, D = x.shape
        Hq, Dh = 16, 256
        Hkv, Sk = k_cache.shape[1], k_cache.shape[2]
        W = min(4096, max(256, Sk // 4))
        rep = Hq // Hkv
        q = (lambda x, *d: x.permute(*d))((x @ wq).reshape(B, Sq, Hq, Dh), 0, 2, 1, 3)
        k = (lambda x, n, axis: torch.repeat_interleave(x, n, dim=axis))(k_cache[:, :, Sk - W:, :], rep, axis=1)
        v = (lambda x, n, axis: torch.repeat_interleave(x, n, dim=axis))(v_cache[:, :, Sk - W:, :], rep, axis=1)
        scores = torch.einsum("bhqd,bhkd->bhqk", q, k) * (Dh ** -0.5)
        p = _softmax(scores, axis=-1)
        o = torch.einsum("bhqk,bhkd->bhqd", p, v)
        return (lambda x, *d: x.permute(*d))(o, 0, 2, 1, 3).reshape(B, Sq, Hq * Dh) @ wo

    a = _A_ref(A_x, A_k_cache, A_v_cache, A_wq, A_wo)
    b = _B_ref(B_x, B_k_cache, B_v_cache, B_wq, B_wo)
    return torch.concatenate([a, b], axis=-1)
```

```cpp
#include <cuda_runtime.h>
#include <cuda.h>
#include <cuda_bf16.h>
#include <stdint.h>

#define W_MAIN 7
#define W_WO 4
#define W_MIN 3
#define W_MAX 12
#define PACE_S 8
#define PACE_FROM 8
#define PACE_SH 1

namespace {

constexpr int NCTA = 128;
constexpr int NTHR = 288;
constexpr int SLOT = 8192;
constexpr int SM_RED = 24 * SLOT;
constexpr int SM_QS = SM_RED + 16384;
constexpr int SM_ML = SM_QS + 2048;
constexpr int SM_OS = SM_ML + 256;
constexpr int SM_BAR = SM_OS + 256;
constexpr int SM_FLAG = SM_BAR + 384;
constexpr int SM_TOTAL = SM_FLAG + 16 + 1024;
constexpr int REC_W = 72;
constexpr int SPIN_LIMIT = 1 << 20;

constexpr int Q_WORDS = 2 * 2 * 2048;
constexpr int REC_WORDS = 2 * 2 * 16 * 4 * 8 * REC_W;
constexpr int OUTP_WORDS = 2 * 2 * 56 * 64 * 8;
constexpr int PACE_WORDS = 32;

struct alignas(64) Maps {
    CUtensorMap m[6];
};

constexpr int SCRATCH_WORDS = Q_WORDS + REC_WORDS + OUTP_WORDS + PACE_WORDS;
__device__ __align__(128) uint32_t g_scratch[SCRATCH_WORDS];

#define TS(i) do { } while (0)
#define TSP(i) do { } while (0)
#define TSQ() do { } while (0)

__device__ __forceinline__ uint32_t enc(uint32_t bits) { return max(~bits, 1u); }
__device__ __forceinline__ uint32_t encf(float f) { return enc(__float_as_uint(f)); }
__device__ __forceinline__ float decf(uint32_t w) { return __uint_as_float(~w); }

__device__ __forceinline__ uint32_t ld_poll(const uint32_t* p) {
    uint32_t v;
    asm volatile("ld.relaxed.gpu.global.u32 %0, [%1];" : "=r"(v) : "l"(p) : "memory");
    return v;
}
__device__ __forceinline__ uint2 ld_poll2(const uint32_t* p) {
    uint2 v;
    asm volatile("ld.relaxed.gpu.global.v2.u32 {%0,%1}, [%2];" : "=r"(v.x), "=r"(v.y) : "l"(p) : "memory");
    return v;
}
__device__ __forceinline__ uint4 ld_poll4(const uint32_t* p) {
    uint4 v;
    asm volatile("ld.relaxed.gpu.global.v4.u32 {%0,%1,%2,%3}, [%4];"
                 : "=r"(v.x), "=r"(v.y), "=r"(v.z), "=r"(v.w) : "l"(p) : "memory");
    return v;
}
__device__ __forceinline__ void st_pub(uint32_t* p, uint32_t v) {
    asm volatile("st.relaxed.gpu.global.u32 [%0], %1;" ::"l"(p), "r"(v) : "memory");
}
__device__ __forceinline__ void st_pub_if(bool pred, uint32_t* p, uint32_t v) {
    asm volatile("{\n.reg .pred p;\nsetp.ne.u32 p, %2, 0;\n@p st.relaxed.gpu.global.u32 [%0], %1;\n}"
                 ::"l"(p), "r"(v), "r"((uint32_t)pred) : "memory");
}
__device__ __forceinline__ void st_pub2_if(bool pred, uint32_t* p, uint32_t a, uint32_t b) {
    asm volatile("{\n.reg .pred p;\nsetp.ne.u32 p, %3, 0;\n@p st.relaxed.gpu.global.v2.u32 [%0], {%1,%2};\n}"
                 ::"l"(p), "r"(a), "r"(b), "r"((uint32_t)pred) : "memory");
}
__device__ __forceinline__ void st_zero4(uint32_t* p) {
    asm volatile("st.relaxed.gpu.global.v4.u32 [%0], {%1,%1,%1,%1};" ::"l"(p), "r"(0u) : "memory");
}
__device__ __forceinline__ uint4 ldg_stream(const void* p) {
    uint4 v;
    asm volatile("ld.global.nc.L1::no_allocate.v4.u32 {%0,%1,%2,%3}, [%4];"
                 : "=r"(v.x), "=r"(v.y), "=r"(v.z), "=r"(v.w) : "l"(p));
    return v;
}
__device__ __forceinline__ uint32_t ldg_u32(const void* p) {
    uint32_t v;
    asm volatile("ld.global.nc.u32 %0, [%1];" : "=r"(v) : "l"(p));
    return v;
}

__device__ __forceinline__ void mbar_init(uint32_t bar, uint32_t cnt) {
    asm volatile("mbarrier.init.shared::cta.b64 [%0], %1;" ::"r"(bar), "r"(cnt) : "memory");
}
__device__ __forceinline__ void mbar_expect_tx(uint32_t bar, uint32_t bytes) {
    asm volatile("mbarrier.arrive.expect_tx.shared::cta.b64 _, [%0], %1;" ::"r"(bar), "r"(bytes) : "memory");
}
__device__ __forceinline__ void mbar_arrive(uint32_t bar) {
    asm volatile("mbarrier.arrive.shared::cta.b64 _, [%0];" ::"r"(bar) : "memory");
}
__device__ __forceinline__ bool mbar_try(uint32_t bar, uint32_t parity) {
    uint32_t ok;
    asm volatile("{\n.reg .pred p;\nmbarrier.try_wait.parity.shared::cta.b64 p, [%1], %2;\nselp.u32 %0, 1, 0, p;\n}"
                 : "=r"(ok) : "r"(bar), "r"(parity) : "memory");
    return ok;
}
__device__ __forceinline__ void mbar_wait1(uint32_t bar, uint32_t parity) {
    int it = 0;
#pragma unroll 1
    while (!mbar_try(bar, parity)) { if (++it > SPIN_LIMIT) __trap(); }
}
__device__ __forceinline__ void mbar_wait_warp(uint32_t bar, uint32_t parity) {
    int it = 0;
#pragma unroll 1
    while (!__all_sync(0xffffffffu, mbar_try(bar, parity))) { if (++it > SPIN_LIMIT) __trap(); }
}
__device__ __forceinline__ void tma3d(uint32_t dst, const CUtensorMap* m, int row, uint32_t bar) {
    asm volatile("cp.async.bulk.tensor.3d.shared::cluster.global.mbarrier::complete_tx::bytes [%0], [%1, {%3, %4, %3}], [%2];"
                 ::"r"(dst), "l"(m), "r"(bar), "r"(0), "r"(row) : "memory");
}
__device__ __forceinline__ void bar_consumers() { asm volatile("bar.sync 1, 256;" ::: "memory"); }

__device__ __forceinline__ void ldsm4(uint32_t (&a)[4], uint32_t addr) {
    asm volatile("ldmatrix.sync.aligned.m8n8.x4.shared.b16 {%0,%1,%2,%3}, [%4];"
                 : "=r"(a[0]), "=r"(a[1]), "=r"(a[2]), "=r"(a[3]) : "r"(addr) : "memory");
}
__device__ __forceinline__ void ldsm4t(uint32_t (&a)[4], uint32_t addr) {
    asm volatile("ldmatrix.sync.aligned.m8n8.x4.trans.shared.b16 {%0,%1,%2,%3}, [%4];"
                 : "=r"(a[0]), "=r"(a[1]), "=r"(a[2]), "=r"(a[3]) : "r"(addr) : "memory");
}
__device__ __forceinline__ void mma16816(float (&c)[4], const uint32_t (&a)[4], uint32_t b0, uint32_t b1) {
    asm("mma.sync.aligned.m16n8k16.row.col.f32.bf16.bf16.f32 {%0,%1,%2,%3}, {%4,%5,%6,%7}, {%8,%9}, {%0,%1,%2,%3};"
        : "+f"(c[0]), "+f"(c[1]), "+f"(c[2]), "+f"(c[3])
        : "r"(a[0]), "r"(a[1]), "r"(a[2]), "r"(a[3]), "r"(b0), "r"(b1));
}
__device__ __forceinline__ uint32_t movtrans(uint32_t a) {
    uint32_t d;
    asm volatile("movmatrix.sync.aligned.m8n8.trans.b16 %0, %1;" : "=r"(d) : "r"(a));
    return d;
}
__device__ __forceinline__ float ex2(float x) {
    float y;
    asm("ex2.approx.ftz.f32 %0, %1;" : "=f"(y) : "f"(x));
    return y;
}
__device__ __forceinline__ uint32_t pack_bf16(float lo, float hi) {
    uint32_t d;
    asm("cvt.rn.bf16x2.f32 %0, %1, %2;" : "=r"(d) : "f"(hi), "f"(lo));
    return d;
}
__device__ __forceinline__ float bf_lo(uint32_t w) { return __uint_as_float(w << 16); }
__device__ __forceinline__ float bf_hi(uint32_t w) { return __uint_as_float(w & 0xffff0000u); }

constexpr float SCALE_LOG2 = 1.4426950408889634f / 16.0f;

__global__ void __launch_bounds__(NTHR, 1)
fused_decode_kernel(const void* __restrict__ xA, const void* __restrict__ xB, const void* __restrict__ wqA,
                    const void* __restrict__ wqB, uint32_t* scratch, __nv_bfloat16* outp,
                    const __grid_constant__ Maps P) {
    extern __shared__ uint8_t smem_raw[];
    const int tid = threadIdx.x, w = tid >> 5, lane = tid & 31;
    const int j = blockIdx.x;
    const int op = j >> 6, jj = j & 63;
    const int tm = j >> 3, r = j & 7;
    const int ab = tm >> 3, ag = tm & 7;
    const uint32_t sraw = (uint32_t)__cvta_generic_to_shared(smem_raw);
    uint32_t sbase = (sraw + 1023u) & ~1023u;
    uint8_t* smem = smem_raw + (sbase - sraw);
    asm volatile("" : "+r"(sbase));
    const uint32_t full0 = sbase + SM_BAR, empty0 = full0 + 24 * 8;
    const uint32_t ready = sbase + SM_FLAG;
    TS(0);

    if (w == 8) {
        if (lane < 6) asm volatile("prefetch.tensormap [%0];" ::"l"(&P.m[lane]) : "memory");
        if (lane == 0) {
            mbar_init(ready, 8);
            asm volatile("fence.mbarrier_init.release.cluster;" ::: "memory");
        }
        if (lane == 0) TSP(15);
        __syncthreads_or(0);
        if (lane == 0) TSP(14);
        if (lane == 0) {
            const int rowA = tm * 8192 + r * 128, rowB = rowA + 6144;
            uint32_t* pace = scratch + Q_WORDS + REC_WORDS + OUTP_WORDS;
            int sl = 0;
            uint32_t ph = 0;
            int W = W_MAIN;
            uint32_t seen = 0;
#pragma unroll 1
            for (int q = 0; q < 21; ++q) {
                const int seg = q >= 4;
                const CUtensorMap* map = q < 20 ? &P.m[(seg ? 0 : 2) + (q & 1)] : &P.m[4 + op];
                int row = q < 20 ? (seg ? rowA + ((q - 4) >> 1) * 1024 : rowB + (q >> 1) * 1024) : jj * 64;
                const int rstep = q < 20 ? 16 : 8;
                const uint32_t bytes = q < 20 ? SLOT : 7168;
                if (q == 3) mbar_wait1(ready, 0);
                if (q == 20) W = W_WO;
#pragma unroll 1
                for (int cw = 0; cw < 8; ++cw) {
                    const int i = q * 8 + cw;
                    if (q >= 3) mbar_wait1(empty0 + 8 * sl, ph ^ 1);
                    if ((i & (PACE_S - 1)) == 0 && i >= PACE_FROM + PACE_S && q < 20) {
                        const int lead = (i - PACE_FROM - PACE_S / 2) - (int)(seen * PACE_S / NCTA);
                        W = min(max(W_MAIN - (lead >> PACE_SH), W_MIN), W_MAX);
                    }
                    int jx = sl - W;
                    uint32_t pw = ph;
                    if (jx < 0) { jx += 24; pw ^= 1; }
                    if (i >= W) mbar_wait1(full0 + 8 * jx, pw);
                    mbar_expect_tx(full0 + 8 * sl, bytes);
                    tma3d(sbase + sl * SLOT, map, row, full0 + 8 * sl);
                    if ((i & (PACE_S - 1)) == 0 && i >= PACE_FROM && i < 160 - PACE_S)
                        asm volatile("atom.relaxed.gpu.global.inc.u32 %0, [%1], %2;"
                                     : "=r"(seen) : "l"(pace), "r"(NCTA * ((160 - PACE_FROM) / PACE_S - 1) - 1) : "memory");
                    row += rstep;
                    if (++sl == 24) { sl = 0; ph ^= 1; }
                }
                if (q == 2) TSP(11);
                if (q == 19) TSP(12);
            }
            TSP(13);
        }
        return;
    }

    if (lane == 0) {
#pragma unroll
        for (int s = 0; s < 3; ++s) mbar_init(full0 + 8 * (s * 8 + w), 1);
        asm volatile("fence.mbarrier_init.release.cluster;" ::: "memory");
    }
    const uint32_t z = (uint32_t)__syncthreads_or(0);
    const int rg = w * 4 + (lane >> 3);
    uint4 wv[14];
    {
        const char* wq = (const char*)(op ? wqB : wqA) + (size_t)(rg * 14) * 8192 + jj * 128 + (lane & 7) * 16 + z;
#pragma unroll
        for (int i = 0; i < 14; ++i) wv[i] = ldg_stream(wq + (size_t)i * 8192);
    }
    uint32_t xa[7], xb[7];
    {
        const uint32_t* xp = (const uint32_t*)(op ? xB : xA) + rg * 7 + z;
#pragma unroll
        for (int i = 0; i < 7; ++i) { xa[i] = ldg_u32(xp + i); xb[i] = ldg_u32(xp + 224 + i); }
    }
    uint32_t* const g_q = scratch;
    uint32_t* const g_rec = scratch + Q_WORDS;
    uint32_t* const g_outp = scratch + Q_WORDS + REC_WORDS;

    {
        float acc[2][8];
#pragma unroll
        for (int c = 0; c < 8; ++c) { acc[0][c] = 0.f; acc[1][c] = 0.f; }
#pragma unroll
        for (int i = 0; i < 14; ++i) {
            const float x0 = (i & 1) ? bf_hi(xa[i >> 1]) : bf_lo(xa[i >> 1]);
            const float x1 = (i & 1) ? bf_hi(xb[i >> 1]) : bf_lo(xb[i >> 1]);
            const uint32_t ww[4] = {wv[i].x, wv[i].y, wv[i].z, wv[i].w};
#pragma unroll
            for (int c = 0; c < 4; ++c) {
                const float a = bf_lo(ww[c]), b = bf_hi(ww[c]);
                acc[0][2 * c] = fmaf(x0, a, acc[0][2 * c]); acc[0][2 * c + 1] = fmaf(x0, b, acc[0][2 * c + 1]);
                acc[1][2 * c] = fmaf(x1, a, acc[1][2 * c]); acc[1][2 * c + 1] = fmaf(x1, b, acc[1][2 * c + 1]);
            }
        }
        const bool u16 = lane & 16, u8 = lane & 8;
        float h[8];
#pragma unroll
        for (int c = 0; c < 8; ++c) {
            const float send = u16 ? acc[0][c] : acc[1][c], keep = u16 ? acc[1][c] : acc[0][c];
            h[c] = keep + __shfl_xor_sync(0xffffffffu, send, 16);
        }
        float q4[4];
#pragma unroll
        for (int c = 0; c < 4; ++c) {
            const float send = u8 ? h[c] : h[4 + c], keep = u8 ? h[4 + c] : h[c];
            q4[c] = keep + __shfl_xor_sync(0xffffffffu, send, 8);
        }
        float* qred = reinterpret_cast<float*>(smem + SM_RED);
        *reinterpret_cast<float4*>(qred + w * 128 + (lane >> 4) * 64 + (lane & 7) * 8 + ((lane >> 3) & 1) * 4) =
            make_float4(q4[0], q4[1], q4[2], q4[3]);
        if (lane == 0) {
#pragma unroll
            for (int s = 0; s < 3; ++s) mbar_init(empty0 + 8 * (s * 8 + w), 1);
            asm volatile("fence.mbarrier_init.release.cluster;" ::: "memory");
            mbar_arrive(ready);
        }
        bar_consumers();
        if (tid < 64) {
            float s0 = 0.f, s1 = 0.f;
#pragma unroll
            for (int i = 0; i < 8; ++i) {
                const float2 v = reinterpret_cast<const float2*>(qred + i * 128)[tid];
                s0 += v.x; s1 += v.y;
            }
            st_pub(g_q + (op * 2 + (tid >> 5)) * 2048 + jj * 32 + (tid & 31), enc(pack_bf16(s0, s1)));
        }
    }
    TS(1);

    uint32_t* qs = reinterpret_cast<uint32_t*>(smem + SM_QS);
    {
        const uint32_t* qB = g_q + (2 + ab) * 2048 + ag * 256 + tid;
        const uint32_t* qA = g_q + ab * 2048 + ag * 256 + tid;
        uint32_t a = 0, b = 0;
        int it = 0;
#pragma unroll 1
        while (true) {
            if (!b) b = ld_poll(qB);
            if (!a) a = ld_poll(qA);
            if (__all_sync(0xffffffffu, a && b)) break;
            if (++it > SPIN_LIMIT) __trap();
            __nanosleep(40);
        }
        qs[tid] = ~b;
        qs[256 + tid] = ~a;
        bar_consumers();
    }
    TS(2);

    const uint32_t ring = sbase + w * SLOT;
    const uint32_t fullw = full0 + 8 * w, emptyw = empty0 + 8 * w;
    const int g = lane >> 2, t = lane & 3;
    uint32_t koff[4], voff[4];
    {
        const int kkey = (lane & 7) + 8 * ((lane >> 3) & 1), khi = lane >> 4;
        const int vkey = (lane & 7) + 8 * (lane >> 4), vhi = (lane >> 3) & 1;
#pragma unroll
        for (int c = 0; c < 4; ++c) {
            koff[c] = kkey * 128 + (((2 * c + khi) ^ (lane & 7)) << 4);
            voff[c] = vkey * 128 + (((2 * c + vhi) ^ (lane & 7)) << 4);
        }
    }
    int s3 = 0;
    uint32_t ph = 0;
#pragma unroll 1
    for (int seg = 0; seg < 2; ++seg) {
        float o[16][4];
        uint32_t qf[32];
#pragma unroll
        for (int i = 0; i < 16; ++i) { o[i][0] = 0.f; o[i][1] = 0.f; o[i][2] = 0.f; o[i][3] = 0.f; }
        float m0 = -INFINITY, m1 = -INFINITY, l0 = 0.f, l1 = 0.f;
#pragma unroll
        for (int ks = 0; ks < 16; ++ks) {
            const uint32_t a = qs[seg * 256 + (g & 1) * 128 + ks * 8 + t], b = qs[seg * 256 + (g & 1) * 128 + ks * 8 + 4 + t];
            qf[2 * ks] = g < 2 ? a : 0u; qf[2 * ks + 1] = g < 2 ? b : 0u;
        }
        const int nit = seg ? 8 : 2;
#pragma unroll 1
        for (int it = 0; it < nit; ++it) {
            float sc[4];
            {
                const uint32_t slot = ring + s3 * (8 * SLOT);
                mbar_wait_warp(fullw + 64 * s3, ph);
                TSQ();
                float acc[4][4];
#pragma unroll
                for (int c = 0; c < 4; ++c) { acc[c][0] = 0.f; acc[c][1] = 0.f; acc[c][2] = 0.f; acc[c][3] = 0.f; }
#pragma unroll
                for (int ks = 0; ks < 16; ++ks) {
                    uint32_t a[4];
                    ldsm4(a, slot + (ks >> 2) * 2048 + koff[ks & 3]);
                    mma16816(acc[ks & 3], a, qf[2 * ks], qf[2 * ks + 1]);
                }
                __syncwarp();
                if (lane == 0) mbar_arrive(emptyw + 64 * s3);
                if (++s3 == 3) { s3 = 0; ph ^= 1; }
#pragma unroll
                for (int i = 0; i < 4; ++i) sc[i] = (acc[0][i] + acc[1][i]) + (acc[2][i] + acc[3][i]);
            }
            float mx0 = fmaxf(sc[0], sc[2]), mx1 = fmaxf(sc[1], sc[3]);
#pragma unroll
            for (int x = 4; x <= 16; x <<= 1) {
                mx0 = fmaxf(mx0, __shfl_xor_sync(0xffffffffu, mx0, x));
                mx1 = fmaxf(mx1, __shfl_xor_sync(0xffffffffu, mx1, x));
            }
            const float mn0 = fmaxf(m0, mx0 * SCALE_LOG2), mn1 = fmaxf(m1, mx1 * SCALE_LOG2);
            const float al0 = ex2(m0 - mn0), al1 = ex2(m1 - mn1);
            const float p0 = ex2(fmaf(sc[0], SCALE_LOG2, -mn0)), p1 = ex2(fmaf(sc[1], SCALE_LOG2, -mn1));
            const float p2 = ex2(fmaf(sc[2], SCALE_LOG2, -mn0)), p3 = ex2(fmaf(sc[3], SCALE_LOG2, -mn1));
            m0 = mn0; m1 = mn1;
            l0 = fmaf(l0, al0, p0 + p2);
            l1 = fmaf(l1, al1, p1 + p3);
            const uint32_t pb0 = movtrans(pack_bf16(p0, p1));
            const uint32_t pb1 = movtrans(pack_bf16(p2, p3));
#pragma unroll
            for (int i = 0; i < 16; ++i) { o[i][0] *= al0; o[i][1] *= al1; o[i][2] *= al0; o[i][3] *= al1; }
            {
                const uint32_t slot = ring + s3 * (8 * SLOT);
                mbar_wait_warp(fullw + 64 * s3, ph);
                TSQ();
#pragma unroll
                for (int mt = 0; mt < 16; ++mt) {
                    uint32_t a[4];
                    ldsm4t(a, slot + (mt >> 2) * 2048 + voff[mt & 3]);
                    mma16816(o[mt], a, pb0, pb1);
                }
                __syncwarp();
                if (lane == 0) mbar_arrive(emptyw + 64 * s3);
                if (++s3 == 3) { s3 = 0; ph ^= 1; }
            }
        }
        if (seg) TS(5); else TS(3);

        uint8_t* red = seg ? smem : smem + SM_RED;
        const int rstride = seg ? SLOT : 2048;
        float4* ml = reinterpret_cast<float4*>(smem + SM_ML) + seg * 8;
#pragma unroll
        for (int x = 4; x <= 16; x <<= 1) {
            l0 += __shfl_xor_sync(0xffffffffu, l0, x);
            l1 += __shfl_xor_sync(0xffffffffu, l1, x);
        }
        if (t == 0) {
            float2* dst = reinterpret_cast<float2*>(red + w * rstride);
#pragma unroll
            for (int mt = 0; mt < 16; ++mt) {
                dst[mt * 16 + g] = make_float2(o[mt][0], o[mt][1]);
                dst[mt * 16 + 8 + g] = make_float2(o[mt][2], o[mt][3]);
            }
            if (lane == 0) ml[w] = make_float4(m0, m1, l0, l1);
        }
        bar_consumers();
        float4 mw[8];
        float2 rv[8];
#pragma unroll
        for (int i = 0; i < 8; ++i) { mw[i] = ml[i]; rv[i] = reinterpret_cast<const float2*>(red + i * rstride)[tid]; }
        float M0 = mw[0].x, M1 = mw[0].y;
#pragma unroll
        for (int i = 1; i < 8; ++i) { M0 = fmaxf(M0, mw[i].x); M1 = fmaxf(M1, mw[i].y); }
        float O0 = 0.f, O1 = 0.f, L0 = 0.f, L1 = 0.f;
#pragma unroll
        for (int i = 0; i < 8; ++i) {
            const float a0 = ex2(mw[i].x - M0), a1 = ex2(mw[i].y - M1);
            O0 = fmaf(a0, rv[i].x, O0); O1 = fmaf(a1, rv[i].y, O1);
            L0 = fmaf(a0, mw[i].z, L0); L1 = fmaf(a1, mw[i].w, L1);
        }
        const int dblk = tid >> 6, dd = tid & 63;
        uint32_t* rec0 = g_rec + (((((1 - seg) * 2 + ab) * 16 + 2 * ag) * 4 + dblk) * 8 + r) * REC_W;
        uint32_t* rec1 = rec0 + 4 * 8 * REC_W;
        st_pub(rec0 + dd, encf(O0));
        st_pub(rec1 + dd, encf(O1));
        st_pub_if(dd < 8, rec0 + 64 + dd, encf(dd == 0 ? M0 : L0));
        st_pub_if(dd < 8, rec1 + 64 + dd, encf(dd == 0 ? M1 : L1));
        if (seg) TS(6); else TS(4);
    }

    const int oh = jj >> 2, odb = jj & 3;
    const int b1 = tid >> 7, dq = (tid & 127) >> 3, sp = tid & 7;
    uint32_t* myrec = g_rec + (((((op * 2 + b1) * 16 + oh) * 4 + odb) * 8) + sp) * REC_W;
    {
        uint4 v = make_uint4(0, 0, 0, 0);
        uint2 ml = make_uint2(0, 0);
        int it = 0;
#pragma unroll 1
        while (true) {
            v = ld_poll4(myrec + dq * 4);
            ml = ld_poll2(myrec + 64);
            if (__all_sync(0xffffffffu, v.x && v.y && v.z && v.w && ml.x && ml.y)) break;
            if (++it > SPIN_LIMIT) __trap();
            __nanosleep(40);
        }
        const float m = decf(ml.x), l = decf(ml.y);
        float M = m;
#pragma unroll
        for (int x = 1; x <= 4; x <<= 1) M = fmaxf(M, __shfl_xor_sync(0xffffffffu, M, x));
        const float a = ex2(m - M);
        float L = a * l, o0 = a * decf(v.x), o1 = a * decf(v.y), o2 = a * decf(v.z), o3 = a * decf(v.w);
#pragma unroll
        for (int x = 1; x <= 4; x <<= 1) {
            L += __shfl_xor_sync(0xffffffffu, L, x);
            o0 += __shfl_xor_sync(0xffffffffu, o0, x);
            o1 += __shfl_xor_sync(0xffffffffu, o1, x);
            o2 += __shfl_xor_sync(0xffffffffu, o2, x);
            o3 += __shfl_xor_sync(0xffffffffu, o3, x);
        }
        const float inv = 1.0f / L;
        const uint2 pk = make_uint2(pack_bf16(o0 * inv, o1 * inv), pack_bf16(o2 * inv, o3 * inv));
        if (sp == 0) *reinterpret_cast<uint2*>(smem + SM_OS + b1 * 128 + dq * 8) = pk;
    }
    TS(7);
    bar_consumers();
    mbar_wait_warp(full0 + 8 * (16 + (lane & 7)), 0);
    TS(8);

    {
        const uint32_t* os = reinterpret_cast<const uint32_t*>(smem + SM_OS);
        uint32_t bw[7][2][4];
        const uint32_t wbase = sbase + (16 + (lane >> 3)) * SLOT + (lane & 7) * 128;
#pragma unroll
        for (int nt = 0; nt < 7; ++nt) {
            const int c = 7 * w + nt;
            const uint32_t off = (c >> 3) * 1024 + (((c & 7) ^ (lane & 7)) << 4);
            ldsm4t(bw[nt][0], wbase + off);
            ldsm4t(bw[nt][1], wbase + 4 * SLOT + off);
        }
        uint32_t af[4][4];
#pragma unroll
        for (int ks = 0; ks < 4; ++ks) {
            const uint32_t a = os[(g & 1) * 32 + ks * 8 + t], b = os[(g & 1) * 32 + ks * 8 + 4 + t];
            af[ks][0] = g < 2 ? a : 0u; af[ks][2] = g < 2 ? b : 0u;
            af[ks][1] = 0u; af[ks][3] = 0u;
        }
        float c[7][4], c2[7][4];
#pragma unroll
        for (int nt = 0; nt < 7; ++nt) {
            c[nt][0] = c[nt][1] = c[nt][2] = c[nt][3] = 0.f;
            c2[nt][0] = c2[nt][1] = c2[nt][2] = c2[nt][3] = 0.f;
            mma16816(c[nt], af[0], bw[nt][0][0], bw[nt][0][1]);
            mma16816(c2[nt], af[1], bw[nt][0][2], bw[nt][0][3]);
        }
#pragma unroll
        for (int nt = 0; nt < 7; ++nt) {
            mma16816(c[nt], af[2], bw[nt][1][0], bw[nt][1][1]);
            mma16816(c2[nt], af[3], bw[nt][1][2], bw[nt][1][3]);
        }
        uint32_t* dst = g_outp + ((op * 2 + (g & 1)) * 56 + 7 * w) * 512 + jj * 8 + 2 * t;
#pragma unroll
        for (int nt = 0; nt < 7; ++nt)
            st_pub2_if(g < 2, dst + nt * 512, encf(c[nt][0] + c2[nt][0]), encf(c[nt][1] + c2[nt][1]));
    }
    TS(9);

    st_zero4(myrec + dq * 4);
    if (dq < 2) st_zero4(myrec + 64 + dq * 4);
    if (tid < 16) st_zero4(g_q + (op * 2 + (tid >> 3)) * 2048 + jj * 32 + (tid & 7) * 4);

    const int task = jj + 64 * w;
    if (w < 2 && task < 112) {
        const int fb = task / 56, cb = task - fb * 56;
        uint32_t* src = g_outp + ((op * 2 + fb) * 56 + cb) * 512 + lane * 4;
        uint4 v[4];
        int it = 0;
#pragma unroll 1
        while (true) {
            bool all = true;
#pragma unroll
            for (int i = 0; i < 4; ++i) v[i] = ld_poll4(src + i * 128);
#pragma unroll
            for (int i = 0; i < 4; ++i) all = all && v[i].x && v[i].y && v[i].z && v[i].w;
            if (__all_sync(0xffffffffu, all)) break;
            if (++it > SPIN_LIMIT) __trap();
            __nanosleep(20);
        }
        float a0 = 0.f, a1 = 0.f, a2 = 0.f, a3 = 0.f;
#pragma unroll
        for (int i = 0; i < 4; ++i) { a0 += decf(v[i].x); a1 += decf(v[i].y); a2 += decf(v[i].z); a3 += decf(v[i].w); }
        const bool u16 = lane & 16, u8 = lane & 8;
        float h0 = (u16 ? a2 : a0) + __shfl_xor_sync(0xffffffffu, u16 ? a0 : a2, 16);
        float h1 = (u16 ? a3 : a1) + __shfl_xor_sync(0xffffffffu, u16 ? a1 : a3, 16);
        float z = (u8 ? h1 : h0) + __shfl_xor_sync(0xffffffffu, u8 ? h0 : h1, 8);
        z += __shfl_xor_sync(0xffffffffu, z, 4);
        z += __shfl_xor_sync(0xffffffffu, z, 2);
        if ((lane & 6) == 0) {
            const int col = 4 * (lane & 1) + 2 * (lane >> 4) + ((lane >> 3) & 1);
            outp[fb * 896 + op * 448 + cb * 8 + col] = __float2bfloat16_rn(z);
        }
#pragma unroll
        for (int i = 0; i < 4; ++i) st_zero4(src + i * 128);
    }
    TS(10);
}

typedef CUresult (*EncodeTiledFn)(CUtensorMap*, CUtensorMapDataType, cuuint32_t, void*, const cuuint64_t*,
                                  const cuuint64_t*, const cuuint32_t*, const cuuint32_t*, CUtensorMapInterleave,
                                  CUtensorMapSwizzle, CUtensorMapL2promotion, CUtensorMapFloatOOBfill);

}

extern "C" void kernel_launch(void* const* d_in, const int* in_sizes, int n_in, void* d_out, int out_size) {
    (void)in_sizes; (void)n_in; (void)out_size;
    static EncodeTiledFn encode = nullptr;
    static uint32_t* scratch = nullptr;
    if (!encode) {
        void* fn = nullptr;
        cudaDriverEntryPointQueryResult qr;
        cudaGetDriverEntryPoint("cuTensorMapEncodeTiled", &fn, cudaEnableDefault, &qr);
        encode = (EncodeTiledFn)fn;
        void* sp = nullptr;
        cudaGetSymbolAddress(&sp, g_scratch);
        scratch = (uint32_t*)sp;
        cudaFuncSetAttribute(fused_decode_kernel, cudaFuncAttributeMaxDynamicSharedMemorySize, SM_TOTAL);
    }
    Maps P;
    for (int p = 0; p < 2; ++p) {
        for (int kv = 0; kv < 2; ++kv) {
            const cuuint64_t dims[3] = {64, 131072, 4};
            const cuuint64_t strides[2] = {512, 128};
            const cuuint32_t box[3] = {64, 16, 4};
            const cuuint32_t es[3] = {1, 1, 1};
            encode(&P.m[2 * p + kv], CU_TENSOR_MAP_DATA_TYPE_BFLOAT16, 3, d_in[5 * p + 1 + kv], dims, strides, box, es,
                   CU_TENSOR_MAP_INTERLEAVE_NONE, CU_TENSOR_MAP_SWIZZLE_128B, CU_TENSOR_MAP_L2_PROMOTION_NONE,
                   CU_TENSOR_MAP_FLOAT_OOB_FILL_NONE);
        }
        const cuuint64_t dims[3] = {64, 4096, 7};
        const cuuint64_t strides[2] = {896, 128};
        const cuuint32_t box[3] = {64, 8, 7};
        const cuuint32_t es[3] = {1, 1, 1};
        encode(&P.m[4 + p], CU_TENSOR_MAP_DATA_TYPE_BFLOAT16, 3, d_in[5 * p + 4], dims, strides, box, es,
               CU_TENSOR_MAP_INTERLEAVE_NONE, CU_TENSOR_MAP_SWIZZLE_128B, CU_TENSOR_MAP_L2_PROMOTION_NONE,
               CU_TENSOR_MAP_FLOAT_OOB_FILL_NONE);
    }
    fused_decode_kernel<<<NCTA, NTHR, SM_TOTAL, cudaStreamPerThread>>>(d_in[0], d_in[5], d_in[3], d_in[8], scratch,
                                                                       (__nv_bfloat16*)d_out, P);
}
```

```cpp
#include <cuda_runtime.h>
#include <cuda.h>
#include <cuda_bf16.h>
#include <stdint.h>

#define W_MAIN 7
#define W_WO 7
#define W_T18 W_MAIN
#define W_T19 W_MAIN

#define W_MIN 3
#define W_MAX 12
#define PACE_MODE 3
#define PACE_INC 2
#define PACE_RND 0
#define PACE_Q0 1
#define PACE_SH 2
#define NS_PACE 200
#define WO_POS 0
#define WO_WT 7
#define W_HI_WO 14
#define W_LO 3
#define W_HI 12
#define PACE_OFF 0
#define PACE_AGE 0.5f
#define WO_BURST 8
#define RHO0 3.65f
#define RHO_A 0.25f

#define EVICT_FIRST 1
#define V_PROMO CU_TENSOR_MAP_L2_PROMOTION_L2_128B
#define ORDER 3
#define W_V W_MAIN
#define W_WOA W_MAIN
#define NS_Q 40
#define NS_REC 40
#define NS_FIN 0
#define POLL_SLEEP(ns) do { if ((ns) > 0) __nanosleep(ns); } while (0)

namespace {

constexpr int NCTA = 128;
constexpr int NTHR = 320;
constexpr int SLOT = 8192;
constexpr int SM_RED = 24 * SLOT;
constexpr int SM_SC = SM_RED + 16384;
constexpr int SM_OR = SM_SC + 2048;
constexpr int SM_QS = SM_OR + 2048;
constexpr int SM_ML = SM_QS + 2048;
constexpr int SM_OS = SM_ML + 128;
constexpr int SM_BAR = SM_OS + 128;
constexpr int SM_FLAG = SM_BAR + 384;
constexpr int SM_TOTAL = SM_FLAG + 32 + 1024;
constexpr int SPIN_LIMIT = 1 << 20;
constexpr int NQ = 22;
constexpr int Q_WOA = 18, Q_WOB = 21 - WO_POS;

constexpr int Q_WORDS = 2 * 2 * 2048;
constexpr int P_WORDS = 16 * 2048;
constexpr int ML_WORDS = 16 * 64 * 4;
constexpr int REC_CTA = 640;
constexpr int REC_WORDS = NCTA * REC_CTA;
constexpr int OUTP_WORDS = 2 * 2 * 56 * 64 * 8;
constexpr int OFF_P = Q_WORDS, OFF_ML = OFF_P + P_WORDS, OFF_REC = OFF_ML + ML_WORDS, OFF_OUTP = OFF_REC + REC_WORDS;
constexpr int OFF_PACE = OFF_OUTP + OUTP_WORDS;
constexpr int PACE_WORDS = 64;

struct alignas(64) Maps {
    CUtensorMap m[8];
};

constexpr int SCRATCH_WORDS = OFF_PACE + PACE_WORDS;
__device__ __align__(128) uint32_t g_scratch[SCRATCH_WORDS];

#define TSX(i) do { } while (0)
#define TS(i) do { } while (0)
#define TSP(i) do { } while (0)
#define TSQ() do { } while (0)

__device__ __forceinline__ uint32_t enc(uint32_t bits) { return max(~bits, 1u); }
__device__ __forceinline__ uint32_t encf(float f) { return enc(__float_as_uint(f)); }
__device__ __forceinline__ float decf(uint32_t w) { return __uint_as_float(~w); }

__device__ __forceinline__ uint32_t ld_poll(const uint32_t* p) {
    uint32_t v;
    asm volatile("ld.relaxed.gpu.global.u32 %0, [%1];" : "=r"(v) : "l"(p) : "memory");
    return v;
}
__device__ __forceinline__ uint2 ld_poll2(const uint32_t* p) {
    uint2 v;
    asm volatile("ld.relaxed.gpu.global.v2.u32 {%0,%1}, [%2];" : "=r"(v.x), "=r"(v.y) : "l"(p) : "memory");
    return v;
}
__device__ __forceinline__ uint4 ld_poll4(const uint32_t* p) {
    uint4 v;
    asm volatile("ld.relaxed.gpu.global.v4.u32 {%0,%1,%2,%3}, [%4];"
                 : "=r"(v.x), "=r"(v.y), "=r"(v.z), "=r"(v.w) : "l"(p) : "memory");
    return v;
}
__device__ __forceinline__ void st_zero4_if(bool pred, uint32_t* p) {
    asm volatile("{\n.reg .pred p;\nsetp.ne.u32 p, %2, 0;\n@p st.relaxed.gpu.global.v4.u32 [%0], {%1,%1,%1,%1};\n}"
                 ::"l"(p), "r"(0u), "r"((uint32_t)pred) : "memory");
}
__device__ __forceinline__ void st_pub(uint32_t* p, uint32_t v) {
    asm volatile("st.relaxed.gpu.global.u32 [%0], %1;" ::"l"(p), "r"(v) : "memory");
}
__device__ __forceinline__ void st_pub_if(bool pred, uint32_t* p, uint32_t v) {
    asm volatile("{\n.reg .pred p;\nsetp.ne.u32 p, %2, 0;\n@p st.relaxed.gpu.global.u32 [%0], %1;\n}"
                 ::"l"(p), "r"(v), "r"((uint32_t)pred) : "memory");
}
__device__ __forceinline__ void st_pub2_if(bool pred, uint32_t* p, uint32_t a, uint32_t b) {
    asm volatile("{\n.reg .pred p;\nsetp.ne.u32 p, %3, 0;\n@p st.relaxed.gpu.global.v2.u32 [%0], {%1,%2};\n}"
                 ::"l"(p), "r"(a), "r"(b), "r"((uint32_t)pred) : "memory");
}
__device__ __forceinline__ void st_pub4_if(bool pred, uint32_t* p, uint32_t a, uint32_t b, uint32_t c, uint32_t d) {
    asm volatile("{\n.reg .pred p;\nsetp.ne.u32 p, %5, 0;\n@p st.relaxed.gpu.global.v4.u32 [%0], {%1,%2,%3,%4};\n}"
                 ::"l"(p), "r"(a), "r"(b), "r"(c), "r"(d), "r"((uint32_t)pred) : "memory");
}
__device__ __forceinline__ void st_zero4(uint32_t* p) {
    asm volatile("st.relaxed.gpu.global.v4.u32 [%0], {%1,%1,%1,%1};" ::"l"(p), "r"(0u) : "memory");
}
__device__ __forceinline__ uint32_t ldg_u32(const void* p) {
    uint32_t v;
    asm volatile("ld.global.u32 %0, [%1];" : "=r"(v) : "l"(p) : "memory");
    return v;
}

__device__ __forceinline__ void mbar_init(uint32_t bar, uint32_t cnt) {
    asm volatile("mbarrier.init.shared::cta.b64 [%0], %1;" ::"r"(bar), "r"(cnt) : "memory");
}
__device__ __forceinline__ void mbar_expect_tx(uint32_t bar, uint32_t bytes) {
    asm volatile("mbarrier.arrive.expect_tx.shared::cta.b64 _, [%0], %1;" ::"r"(bar), "r"(bytes) : "memory");
}
__device__ __forceinline__ void mbar_arrive(uint32_t bar) {
    asm volatile("mbarrier.arrive.shared::cta.b64 _, [%0];" ::"r"(bar) : "memory");
}
__device__ __forceinline__ bool mbar_try(uint32_t bar, uint32_t parity) {
    uint32_t ok;
    asm volatile("{\n.reg .pred p;\nmbarrier.try_wait.parity.shared::cta.b64 p, [%1], %2;\nselp.u32 %0, 1, 0, p;\n}"
                 : "=r"(ok) : "r"(bar), "r"(parity) : "memory");
    return ok;
}
__device__ __forceinline__ bool mbar_test(uint32_t bar, uint32_t parity) {
    uint32_t ok;
    asm volatile("{\n.reg .pred p;\nmbarrier.test_wait.parity.shared::cta.b64 p, [%1], %2;\nselp.u32 %0, 1, 0, p;\n}"
                 : "=r"(ok) : "r"(bar), "r"(parity) : "memory");
    return ok;
}
__device__ __forceinline__ void mbar_wait1(uint32_t bar, uint32_t parity) {
    int it = 0;
#pragma unroll 1
    while (!mbar_try(bar, parity)) { if (++it > SPIN_LIMIT) __trap(); }
}
__device__ __forceinline__ void mbar_wait_warp(uint32_t bar, uint32_t parity) {
    int it = 0;
#pragma unroll 1
    while (!__all_sync(0xffffffffu, mbar_try(bar, parity))) { if (++it > SPIN_LIMIT) __trap(); }
}
__device__ __forceinline__ void tma3d(uint32_t dst, const CUtensorMap* m, int col, int row, int chunk, uint32_t bar, uint64_t pol) {
    asm volatile("cp.async.bulk.tensor.3d.shared::cluster.global.mbarrier::complete_tx::bytes.L2::cache_hint"
                 " [%0], [%1, {%3, %4, %5}], [%2], %6;"
                 ::"r"(dst), "l"(m), "r"(bar), "r"(col), "r"(row), "r"(chunk), "l"(pol) : "memory");
}
__device__ __forceinline__ uint64_t stream_policy() {
    uint64_t pol;
    asm("createpolicy.fractional.L2::evict_first.b64 %0, 1.0;" : "=l"(pol));
    return pol;
}
__device__ __forceinline__ void bar_consumers() { asm volatile("bar.sync 1, 256;" ::: "memory"); }

__device__ __forceinline__ void ldsm4(uint32_t (&a)[4], uint32_t addr) {
    asm volatile("ldmatrix.sync.aligned.m8n8.x4.shared.b16 {%0,%1,%2,%3}, [%4];"
                 : "=r"(a[0]), "=r"(a[1]), "=r"(a[2]), "=r"(a[3]) : "r"(addr) : "memory");
}
__device__ __forceinline__ void ldsm4t(uint32_t (&a)[4], uint32_t addr) {
    asm volatile("ldmatrix.sync.aligned.m8n8.x4.trans.shared.b16 {%0,%1,%2,%3}, [%4];"
                 : "=r"(a[0]), "=r"(a[1]), "=r"(a[2]), "=r"(a[3]) : "r"(addr) : "memory");
}
__device__ __forceinline__ void mma16816(float (&c)[4], const uint32_t (&a)[4], uint32_t b0, uint32_t b1) {
    asm("mma.sync.aligned.m16n8k16.row.col.f32.bf16.bf16.f32 {%0,%1,%2,%3}, {%4,%5,%6,%7}, {%8,%9}, {%0,%1,%2,%3};"
        : "+f"(c[0]), "+f"(c[1]), "+f"(c[2]), "+f"(c[3])
        : "r"(a[0]), "r"(a[1]), "r"(a[2]), "r"(a[3]), "r"(b0), "r"(b1));
}
__device__ __forceinline__ uint32_t movtrans(uint32_t a) {
    uint32_t d;
    asm volatile("movmatrix.sync.aligned.m8n8.trans.b16 %0, %1;" : "=r"(d) : "r"(a));
    return d;
}
__device__ __forceinline__ float ex2(float x) {
    float y;
    asm("ex2.approx.ftz.f32 %0, %1;" : "=f"(y) : "f"(x));
    return y;
}
__device__ __forceinline__ uint32_t pack_bf16(float lo, float hi) {
    uint32_t d;
    asm("cvt.rn.bf16x2.f32 %0, %1, %2;" : "=r"(d) : "f"(hi), "f"(lo));
    return d;
}
__device__ __forceinline__ float bf_lo(uint32_t w) { return __uint_as_float(w << 16); }
__device__ __forceinline__ float bf_hi(uint32_t w) { return __uint_as_float(w & 0xffff0000u); }

constexpr float SCALE_LOG2 = 1.4426950408889634f / 16.0f;

__global__ void __launch_bounds__(NTHR, 1)
fused_decode_kernel(const void* __restrict__ xA, const void* __restrict__ xB, uint32_t* scratch, __nv_bfloat16* outp,
                    const __grid_constant__ Maps P) {
    extern __shared__ uint8_t smem_raw[];
    const int tid = threadIdx.x, w = tid >> 5, lane = tid & 31;
    const int j = blockIdx.x;
    const int op = j >> 6, jj = j & 63;
    const int r = (j & 1) | ((j >> 1) & 6), ab = (j >> 1) & 1, ag = j >> 4;
    const int tm = ab * 8 + ag;
    const uint32_t sraw = (uint32_t)__cvta_generic_to_shared(smem_raw);
    uint32_t sbase = (sraw + 1023u) & ~1023u;
    uint8_t* smem = smem_raw + (sbase - sraw);
    asm volatile("" : "+r"(sbase));
    const uint32_t full0 = sbase + SM_BAR, empty0 = full0 + 24 * 8;
    TS(0);

    const uint64_t pol = stream_policy();
    if (tid == 256) {
        asm volatile("prefetch.tensormap [%0];" ::"l"(&P.m[op]) : "memory");
#pragma unroll
        for (int s = 0; s < 8; ++s) mbar_init(full0 + 8 * s, 1);
        asm volatile("fence.mbarrier_init.release.cluster;" ::: "memory");
        TSP(15);
#pragma unroll 1
        for (int cw = 0; cw < 8; ++cw) {
            mbar_expect_tx(full0 + 8 * cw, 7168);
            tma3d(sbase + cw * SLOT, &P.m[op], 0, cw * 56, jj, full0 + 8 * cw, pol);
        }
    }
    if (tid == 0) {
#pragma unroll
        for (int s = 8; s < 48; ++s) mbar_init(full0 + 8 * s, 1);
        asm volatile("fence.mbarrier_init.release.cluster;" ::: "memory");
    }
    if (w == 8) {
        if (lane >= 2 && lane < 8) asm volatile("prefetch.tensormap [%0];" ::"l"(&P.m[lane]) : "memory");
        __syncwarp();
        asm volatile("bar.sync 2, 320;" ::: "memory");
        if (lane == 0) TSP(14);
        if (lane == 0) {
            const int rowA = tm * 8192, rowB = rowA + 6144;
            uint32_t* pace = scratch + OFF_PACE;
            int sl = 8;
            uint32_t ph = 0;
            int W = W_MAIN;
            int lp = 0, lsl = 0;
            uint32_t lph = 0;
            int lpw = 0, kw = 8 * 16;
#pragma unroll 1
            for (int q = 0; q < NQ; ++q) {
                const CUtensorMap* map;
                int row, rstep = 128, col = 0, Wb = W_V;
                uint32_t bytes = SLOT;
                if (q < 16) { map = &P.m[2 + (q & 1)]; row = rowA + (q >> 1) * 1024 + r * 128; rstep = 16; Wb = W_MAIN; }
                else if (q < 18) { map = &P.m[4]; row = rowB + r * 256 + (q - 16) * 128; rstep = 16; Wb = W_MAIN; }
                else if (q == Q_WOB || q == Q_WOA) {
                    map = &P.m[q == Q_WOB ? 7 : 6]; row = ag * 512 + r * 32; rstep = 8; bytes = 7168;
                    Wb = q == Q_WOB ? W_WO : W_WOA;
                } else { map = &P.m[5]; row = rowB + (q - Q_WOA - 1 - (q > Q_WOB)) * 128; rstep = 256; col = r * 32; }
                const bool iswo = q == Q_WOB || q == Q_WOA;
                const int whi = iswo ? W_HI_WO : W_HI;
                W = Wb;
#pragma unroll 1
                for (int cw = 0; cw < 8; ++cw) {
                    if (q >= 2) mbar_wait1(empty0 + 8 * sl, ph ^ 1);
                    if (!iswo || (cw & (WO_BURST - 1)) == 0) {
                        const int k = q * 8 + 8 + cw;
                        int it = 0;
#pragma unroll 1
                        while (true) {
                            if (lp < k && mbar_test(full0 + 8 * lsl, lph)) {
                                lpw += ((lp >> 3) == Q_WOB + 1 || (lp >> 3) == Q_WOA + 1) ? WO_WT : 16;
                                ++lp;
                                if (++lsl == 24) { lsl = 0; lph ^= 1; }
                                asm volatile("st.volatile.shared.s32 [%0], %1;" ::"r"(sbase + SM_FLAG + 8), "r"(lpw) : "memory");
                                continue;
                            }
                            const int infl = k - lp;
                            if (infl < W_LO) break;
                            if (infl < whi) {
                                uint32_t c0, c1, c2, c3, now;
                                asm volatile("ld.volatile.shared.v4.u32 {%0,%1,%2,%3}, [%4];"
                                             : "=r"(c0), "=r"(c1), "=r"(c2), "=r"(c3) : "r"(sbase + SM_FLAG + 16) : "memory");
                                if (c3 == 0) {
                                    if (infl < Wb) break;
                                } else {
                                    asm volatile("mov.u32 %0, %%clock;" : "=r"(now));
                                    const float est = fmaf((float)min((int)(now - c1), 3500), __uint_as_float(c2), __uint_as_float(c0));
                                    if ((float)((kw - 16 * Wb) * NCTA - 16 * PACE_OFF) <= est) break;
                                }
                            }
                            if (++it > SPIN_LIMIT) __trap();
                        }
                    }
                    mbar_expect_tx(full0 + 8 * sl, bytes);
                    tma3d(sbase + sl * SLOT, map, col, row, 0, full0 + 8 * sl, pol);
                    kw += iswo ? WO_WT : 16;
                    row += rstep;
                    if (rstep == 8 && cw == 3) row += 224;
                    if (++sl == 24) { sl = 0; ph ^= 1; }
                }
                if (q == NQ - 1) asm volatile("st.volatile.shared.s32 [%0], %1;" ::"r"(sbase + SM_FLAG + 4), "r"(1) : "memory");
                if (q == 1) TSP(11);
                if (q == NQ - 2) TSP(12);
            }
            TSP(13);
        }
        return;
    }

    if (w == 9) {
        uint32_t* const pB = scratch + OFF_P + tm * 2048 + r * 256;
        uint32_t* const ml = scratch + OFF_ML + tm * 256 + r * 32;
        uint32_t* const rec_in = scratch + OFF_REC + (tm * 8 + r) * REC_CTA;
        uint32_t* const outp_in = scratch + OFF_OUTP + j * 512;
        uint32_t* const cleared = scratch + OFF_PACE + 32;
        if (lane < 2) asm volatile("st.shared.v4.u32 [%0], {%1, %1, %1, %1};" ::"r"(sbase + SM_FLAG + 16 * lane), "r"(0) : "memory");
        __syncwarp();
        asm volatile("bar.arrive 2, 320;" ::: "memory");
#pragma unroll
        for (int i = 0; i < 2; ++i) st_zero4(pB + i * 128 + lane * 4);
        st_zero4_if(lane < 8, ml + (lane & 7) * 4);
#pragma unroll
        for (int i = 0; i < 5; ++i) st_zero4(rec_in + i * 128 + lane * 4);
#pragma unroll
        for (int i = 0; i < 4; ++i) {
            st_zero4_if(j < 112, outp_in + i * 128 + lane * 4);
            st_zero4_if(j < 112, outp_in + 112 * 512 + i * 128 + lane * 4);
        }
        uint32_t* const prog = scratch + OFF_PACE;
        if (j == 0 && lane == 0) st_pub(prog, 0);
        __syncwarp();
        if (lane == 0) {
            uint32_t c;
            asm volatile("atom.release.gpu.global.add.u32 %0, [%1], 1;" : "=r"(c) : "l"(cleared) : "memory");
            const uint32_t target = (c & ~(uint32_t)(NCTA - 1)) + NCTA;
            int it = 0;
#pragma unroll 1
            while (true) {
                asm volatile("ld.acquire.gpu.global.u32 %0, [%1];" : "=r"(c) : "l"(cleared) : "memory");
                if ((int32_t)(c - target) >= 0) break;
                if (++it > SPIN_LIMIT) __trap();
                __nanosleep(200);
            }
        }
        __syncwarp();
        asm volatile("bar.arrive 3, 288;" ::: "memory");
        if (lane == 0) {
            int last = 0, psum = 0;
            uint32_t pts = 0;
            float rho = RHO0;
#pragma unroll 1
            for (int it = 0; it < 4096; ++it) {
                int own, done, sum;
                uint32_t t0, t1;
                asm volatile("ld.volatile.shared.s32 %0, [%1];" : "=r"(done) : "r"(sbase + SM_FLAG + 4) : "memory");
                if (done) break;
                asm volatile("ld.volatile.shared.s32 %0, [%1];" : "=r"(own) : "r"(sbase + SM_FLAG + 8) : "memory");
                asm volatile("mov.u32 %0, %%clock;" : "=r"(t0));
                asm volatile("atom.relaxed.gpu.global.add.s32 %0, [%1], %2;" : "=r"(sum) : "l"(prog), "r"(own - last) : "memory");
                asm volatile("{\n.reg .u32 t;\nadd.u32 t, %1, 0;\nmov.u32 %0, %%clock;\n}" : "=r"(t1) : "r"(sum) : "memory");
                sum += own - last;
                last = own;
                const uint32_t ts = t0 + ((t1 - t0) >> 1);
                const float per = (float)(int)(ts - pts);
                if (it >= 3) rho += ((float)(sum - psum) / per - rho) * RHO_A;
                const float cur = fmaf(rho * PACE_AGE, per + (float)(int)(t1 - t0), (float)sum);
                psum = sum; pts = ts;
                if (it >= 2)
                    asm volatile("st.volatile.shared.v4.u32 [%0], {%1,%2,%3,%4};"
                                 ::"r"(sbase + SM_FLAG + 16), "r"(__float_as_uint(cur)), "r"(ts), "r"(__float_as_uint(rho)), "r"(1) : "memory");
                __nanosleep(NS_PACE);
            }
        }
        return;
    }

    uint32_t* const g_q = scratch;
    uint32_t* const g_outp = scratch + OFF_OUTP;
    const int g = lane >> 2, t = lane & 3;
    const int rg = w * 4 + (lane >> 3);
    uint32_t xa[7], xb[7];
    {
        const uint32_t* xp = (const uint32_t*)(op ? xB : xA) + rg * 7;
#pragma unroll
        for (int i = 0; i < 7; ++i) { xa[i] = ldg_u32(xp + i); xb[i] = ldg_u32(xp + 224 + i); }
    }
    asm volatile("bar.sync 2, 320;" ::: "memory");
    uint4 wv[14];
    mbar_wait_warp(full0 + 8 * w, 0);
    TS(3);
    {
        const uint4* wq = reinterpret_cast<const uint4*>(smem + w * SLOT) + (lane >> 3) * (14 * 8) + (lane & 7);
#pragma unroll
        for (int i = 0; i < 14; ++i) wv[i] = wq[i * 8];
    }

    {
        float acc[2][8];
#pragma unroll
        for (int c = 0; c < 8; ++c) { acc[0][c] = 0.f; acc[1][c] = 0.f; }
#pragma unroll
        for (int i = 0; i < 14; ++i) {
            const float x0 = (i & 1) ? bf_hi(xa[i >> 1]) : bf_lo(xa[i >> 1]);
            const float x1 = (i & 1) ? bf_hi(xb[i >> 1]) : bf_lo(xb[i >> 1]);
            const uint32_t ww[4] = {wv[i].x, wv[i].y, wv[i].z, wv[i].w};
#pragma unroll
            for (int c = 0; c < 4; ++c) {
                const float a = bf_lo(ww[c]), b = bf_hi(ww[c]);
                acc[0][2 * c] = fmaf(x0, a, acc[0][2 * c]); acc[0][2 * c + 1] = fmaf(x0, b, acc[0][2 * c + 1]);
                acc[1][2 * c] = fmaf(x1, a, acc[1][2 * c]); acc[1][2 * c + 1] = fmaf(x1, b, acc[1][2 * c + 1]);
            }
        }
        __syncwarp();
        if (lane == 0) mbar_arrive(empty0 + 8 * w);
        const bool u16 = lane & 16, u8 = lane & 8;
        float h[8];
#pragma unroll
        for (int c = 0; c < 8; ++c) {
            const float send = u16 ? acc[0][c] : acc[1][c], keep = u16 ? acc[1][c] : acc[0][c];
            h[c] = keep + __shfl_xor_sync(0xffffffffu, send, 16);
        }
        float q4[4];
#pragma unroll
        for (int c = 0; c < 4; ++c) {
            const float send = u8 ? h[c] : h[4 + c], keep = u8 ? h[4 + c] : h[c];
            q4[c] = keep + __shfl_xor_sync(0xffffffffu, send, 8);
        }
        float* qred = reinterpret_cast<float*>(smem + SM_RED);
        *reinterpret_cast<float4*>(qred + w * 128 + (lane >> 4) * 64 + (lane & 7) * 8 + ((lane >> 3) & 1) * 4) =
            make_float4(q4[0], q4[1], q4[2], q4[3]);
        bar_consumers();
        if (tid < 64) {
            float s0 = 0.f, s1 = 0.f;
#pragma unroll
            for (int i = 0; i < 8; ++i) {
                const float2 v = reinterpret_cast<const float2*>(qred + i * 128)[tid];
                s0 += v.x; s1 += v.y;
            }
            st_pub(g_q + (op * 2 + (tid >> 5)) * 2048 + jj * 32 + (tid & 31), enc(pack_bf16(s0, s1)));
        }
    }
    TS(1);

    uint32_t* qs = reinterpret_cast<uint32_t*>(smem + SM_QS);
    {
        const uint32_t* qB = g_q + (2 + ab) * 2048 + ag * 256 + tid;
        const uint32_t* qA = g_q + ab * 2048 + ag * 256 + tid;
        uint32_t a = 0, b = 0;
        int it = 0;
#pragma unroll 1
        while (true) {
            if (!b) b = ld_poll(qB);
            if (!a) a = ld_poll(qA);
            if (__all_sync(0xffffffffu, a && b)) break;
            if (++it > SPIN_LIMIT) __trap();
            POLL_SLEEP(NS_Q);
        }
        qs[tid] = ~b;
        qs[256 + tid] = ~a;
        TSX(0);
        bar_consumers();
    }
    TS(2);
    TSX(1);

    const uint32_t ring = sbase + w * SLOT;
    const uint32_t fullw = full0 + 8 * w, emptyw = empty0 + 8 * w;
    int s3 = 1;
    uint32_t ph = 0;
    uint32_t koff[4];
    {
        const int kkey = (lane & 7) + 8 * ((lane >> 3) & 1), khi = lane >> 4;
#pragma unroll
        for (int c = 0; c < 4; ++c) koff[c] = kkey * 128 + (((2 * c + khi) ^ (lane & 7)) << 4);
    }
    {
        uint32_t voff[4];
        const int vkey = (lane & 7) + 8 * (lane >> 4), vhi = (lane >> 3) & 1;
#pragma unroll
        for (int c = 0; c < 4; ++c) voff[c] = vkey * 128 + (((2 * c + vhi) ^ (lane & 7)) << 4);
        float o[16][4];
        uint32_t qf[32];
#pragma unroll
        for (int i = 0; i < 16; ++i) { o[i][0] = 0.f; o[i][1] = 0.f; o[i][2] = 0.f; o[i][3] = 0.f; }
        float m0 = -INFINITY, m1 = -INFINITY, l0 = 0.f, l1 = 0.f;
#pragma unroll
        for (int ks = 0; ks < 16; ++ks) {
            const uint32_t a = qs[256 + (g & 1) * 128 + ks * 8 + t], b = qs[256 + (g & 1) * 128 + ks * 8 + 4 + t];
            qf[2 * ks] = g < 2 ? a : 0u; qf[2 * ks + 1] = g < 2 ? b : 0u;
        }
#pragma unroll 1
        for (int it = 0; it < 8; ++it) {
            float sc[4];
            {
                const uint32_t slot = ring + s3 * (8 * SLOT);
                mbar_wait_warp(fullw + 64 * s3, ph);
                TSQ();
                float acc[4][4];
#pragma unroll
                for (int c = 0; c < 4; ++c) { acc[c][0] = 0.f; acc[c][1] = 0.f; acc[c][2] = 0.f; acc[c][3] = 0.f; }
#pragma unroll
                for (int ks = 0; ks < 16; ++ks) {
                    uint32_t a[4];
                    ldsm4(a, slot + (ks >> 2) * 2048 + koff[ks & 3]);
                    mma16816(acc[ks & 3], a, qf[2 * ks], qf[2 * ks + 1]);
                }
                __syncwarp();
                if (lane == 0) mbar_arrive(emptyw + 64 * s3);
                if (++s3 == 3) { s3 = 0; ph ^= 1; }
#pragma unroll
                for (int i = 0; i < 4; ++i) sc[i] = (acc[0][i] + acc[1][i]) + (acc[2][i] + acc[3][i]);
            }
            float mx0 = fmaxf(sc[0], sc[2]), mx1 = fmaxf(sc[1], sc[3]);
#pragma unroll
            for (int x = 4; x <= 16; x <<= 1) {
                mx0 = fmaxf(mx0, __shfl_xor_sync(0xffffffffu, mx0, x));
                mx1 = fmaxf(mx1, __shfl_xor_sync(0xffffffffu, mx1, x));
            }
            const float mn0 = fmaxf(m0, mx0 * SCALE_LOG2), mn1 = fmaxf(m1, mx1 * SCALE_LOG2);
            const float al0 = ex2(m0 - mn0), al1 = ex2(m1 - mn1);
            const float p0 = ex2(fmaf(sc[0], SCALE_LOG2, -mn0)), p1 = ex2(fmaf(sc[1], SCALE_LOG2, -mn1));
            const float p2 = ex2(fmaf(sc[2], SCALE_LOG2, -mn0)), p3 = ex2(fmaf(sc[3], SCALE_LOG2, -mn1));
            m0 = mn0; m1 = mn1;
            l0 = fmaf(l0, al0, p0 + p2);
            l1 = fmaf(l1, al1, p1 + p3);
            const uint32_t pb0 = movtrans(pack_bf16(p0, p1));
            const uint32_t pb1 = movtrans(pack_bf16(p2, p3));
#pragma unroll
            for (int i = 0; i < 16; ++i) { o[i][0] *= al0; o[i][1] *= al1; o[i][2] *= al0; o[i][3] *= al1; }
            {
                const uint32_t slot = ring + s3 * (8 * SLOT);
                mbar_wait_warp(fullw + 64 * s3, ph);
                TSQ();
#pragma unroll
                for (int mt = 0; mt < 16; ++mt) {
                    uint32_t a[4];
                    ldsm4t(a, slot + (mt >> 2) * 2048 + voff[mt & 3]);
                    mma16816(o[mt], a, pb0, pb1);
                }
                __syncwarp();
                if (lane == 0) mbar_arrive(emptyw + 64 * s3);
                if (++s3 == 3) { s3 = 0; ph ^= 1; }
            }
        }
        uint8_t* red = smem + SM_RED;
        float4* ml = reinterpret_cast<float4*>(smem + SM_ML);
#pragma unroll
        for (int x = 4; x <= 16; x <<= 1) {
            l0 += __shfl_xor_sync(0xffffffffu, l0, x);
            l1 += __shfl_xor_sync(0xffffffffu, l1, x);
        }
        if (t == 0) {
            float2* dst = reinterpret_cast<float2*>(red + w * 2048);
#pragma unroll
            for (int mt = 0; mt < 16; ++mt) {
                dst[mt * 16 + g] = make_float2(o[mt][0], o[mt][1]);
                dst[mt * 16 + 8 + g] = make_float2(o[mt][2], o[mt][3]);
            }
            if (lane == 0) ml[w] = make_float4(m0, m1, l0, l1);
        }
        asm volatile("bar.sync 3, 288;" ::: "memory");
        float4 mw[8];
        float2 rv[8];
#pragma unroll
        for (int i = 0; i < 8; ++i) { mw[i] = ml[i]; rv[i] = reinterpret_cast<const float2*>(red + i * 2048)[tid]; }
        float M0 = mw[0].x, M1 = mw[0].y;
#pragma unroll
        for (int i = 1; i < 8; ++i) { M0 = fmaxf(M0, mw[i].x); M1 = fmaxf(M1, mw[i].y); }
        float O0 = 0.f, O1 = 0.f, L0 = 0.f, L1 = 0.f;
#pragma unroll
        for (int i = 0; i < 8; ++i) {
            const float a0 = ex2(mw[i].x - M0), a1 = ex2(mw[i].y - M1);
            O0 = fmaf(a0, rv[i].x, O0); O1 = fmaf(a1, rv[i].y, O1);
            L0 = fmaf(a0, mw[i].z, L0); L1 = fmaf(a1, mw[i].w, L1);
        }
        uint32_t* rec = scratch + OFF_REC + (tm * 8 + w) * REC_CTA;
        st_pub(rec + r * 32 + lane, encf(O0));
        st_pub(rec + (8 + r) * 32 + lane, encf(O1));
        st_pub_if(lane < 8, rec + 512 + r * 8 + lane, encf(lane == 0 ? M0 : L0));
        st_pub_if(lane < 8, rec + 512 + (8 + r) * 8 + lane, encf(lane == 0 ? M1 : L1));
    }

    uint32_t* const g_p = scratch + OFF_P + tm * 2048;
    uint32_t* const g_ml = scratch + OFF_ML + tm * 256;
    {
        float* const S = reinterpret_cast<float*>(smem + SM_SC) + w * 64;
        uint32_t qf[32];
#pragma unroll
        for (int ks = 0; ks < 16; ++ks) {
            const uint32_t a = qs[(g & 1) * 128 + ks * 8 + t], b = qs[(g & 1) * 128 + ks * 8 + 4 + t];
            qf[2 * ks] = a; qf[2 * ks + 1] = b;
        }
#pragma unroll 1
        for (int it = 0; it < 2; ++it) {
            const uint32_t slot = ring + s3 * (8 * SLOT);
            mbar_wait_warp(fullw + 64 * s3, ph);
            TSQ();
            float acc[4][4];
#pragma unroll
            for (int c = 0; c < 4; ++c) { acc[c][0] = 0.f; acc[c][1] = 0.f; acc[c][2] = 0.f; acc[c][3] = 0.f; }
#pragma unroll
            for (int ks = 0; ks < 16; ++ks) {
                uint32_t a[4];
                ldsm4(a, slot + (ks >> 2) * 2048 + koff[ks & 3]);
                mma16816(acc[ks & 3], a, qf[2 * ks], qf[2 * ks + 1]);
            }
            __syncwarp();
            if (lane == 0) mbar_arrive(emptyw + 64 * s3);
            if (++s3 == 3) { s3 = 0; ph ^= 1; }
            const float s0 = (acc[0][0] + acc[1][0]) + (acc[2][0] + acc[3][0]), s1 = (acc[0][1] + acc[1][1]) + (acc[2][1] + acc[3][1]);
            const float s2 = (acc[0][2] + acc[1][2]) + (acc[2][2] + acc[3][2]), s3_ = (acc[0][3] + acc[1][3]) + (acc[2][3] + acc[3][3]);
            const float sv = (t & 2) ? ((t & 1) ? s3_ : s2) : ((t & 1) ? s1 : s0);
            S[(t & 1) * 32 + it * 16 + (t >> 1) * 8 + g] = sv;
        }
        __syncwarp();
        const int hd = (lane >> 2) & 1, tt = lane & 3;
        float2 sv[4];
#pragma unroll
        for (int c = 0; c < 4; ++c) sv[c] = *reinterpret_cast<const float2*>(S + hd * 32 + c * 8 + 2 * tt);
        float mx = fmaxf(fmaxf(fmaxf(sv[0].x, sv[0].y), fmaxf(sv[1].x, sv[1].y)), fmaxf(fmaxf(sv[2].x, sv[2].y), fmaxf(sv[3].x, sv[3].y)));
        mx = fmaxf(mx, __shfl_xor_sync(0xffffffffu, mx, 1));
        mx = fmaxf(mx, __shfl_xor_sync(0xffffffffu, mx, 2));
        const float m = mx * SCALE_LOG2;
        float l = 0.f;
        uint32_t pw[4];
#pragma unroll
        for (int c = 0; c < 4; ++c) {
            const float p0 = ex2(fmaf(sv[c].x, SCALE_LOG2, -m)), p1 = ex2(fmaf(sv[c].y, SCALE_LOG2, -m));
            l += p0 + p1;
            pw[c] = enc(pack_bf16(p0, p1));
        }
        l += __shfl_xor_sync(0xffffffffu, l, 1);
        l += __shfl_xor_sync(0xffffffffu, l, 2);
        st_pub4_if(lane < 8, g_p + (r * 8 + w) * 32 + lane * 4, pw[0], pw[1], pw[2], pw[3]);
        st_pub2_if((lane & 27) == 0, g_ml + (r * 8 + w) * 4 + hd * 2, encf(m), encf(l));
    }

    uint32_t voff[2];
    {
        const int vkey = (lane & 7) + 8 * (lane >> 4), vhi = (lane >> 3) & 1;
#pragma unroll
        for (int c = 0; c < 2; ++c) voff[c] = vkey * 64 + (((2 * c + vhi) ^ ((lane >> 1) & 3)) << 4);
    }
    const int wx = w;
    uint32_t bw[2][7][4];
    auto load_wo = [&](int half, int grp, uint32_t par) {
        mbar_wait_warp(full0 + 64 * grp + 8 * (lane & 3) + 32 * half, par);
        const uint32_t wbase = sbase + (grp * 8 + (lane >> 3)) * SLOT + (lane & 7) * 128 + half * 4 * SLOT;
#pragma unroll
        for (int nt = 0; nt < 7; ++nt) {
            const int cc = 7 * wx + nt;
            ldsm4t(bw[half][nt], wbase + (cc >> 3) * 1024 + (((cc & 7) ^ (lane & 7)) << 4));
        }
    };
    auto project = [&](int seg, uint32_t ow, int grp, uint32_t par) {
        uint32_t af[4][4];
#pragma unroll
        for (int ks = 0; ks < 4; ++ks) {
            af[ks][0] = __shfl_sync(0xffffffffu, ow, ks * 8 + t);
            af[ks][2] = __shfl_sync(0xffffffffu, ow, ks * 8 + 4 + t);
            af[ks][1] = 0u; af[ks][3] = 0u;
        }
        float c[7][4], c2[7][4];
#pragma unroll
        for (int half = 0; half < 2; ++half) {
            load_wo(half, grp, par);
#pragma unroll
            for (int nt = 0; nt < 7; ++nt) {
                if (half == 0) {
                    c[nt][0] = c[nt][1] = c[nt][2] = c[nt][3] = 0.f;
                    c2[nt][0] = c2[nt][1] = c2[nt][2] = c2[nt][3] = 0.f;
                }
                mma16816(c[nt], af[2 * half], bw[half][nt][0], bw[half][nt][1]);
                mma16816(c2[nt], af[2 * half + 1], bw[half][nt][2], bw[half][nt][3]);
            }
        }
        float v0 = c[0][0] + c2[0][0], v1 = c[0][1] + c2[0][1];
#pragma unroll
        for (int nt = 1; nt < 7; ++nt) {
            const float u0 = c[nt][0] + c2[nt][0], u1 = c[nt][1] + c2[nt][1];
            v0 = g == nt ? u0 : v0; v1 = g == nt ? u1 : v1;
        }
        uint32_t* dst = g_outp + ((seg * 2 + ab) * 56 + 7 * wx + g) * 512 + (ag * 8 + r) * 8 + 2 * t;
        st_pub2_if(g < 7, dst, encf(v0), encf(v1));
    };
#pragma unroll 1
    for (int seg = 0; seg < 2; ++seg) {
        uint32_t ow;
        if (seg == 0) {
            if (w < 4) {
                const int hh = tid >> 6, dq = (tid >> 3) & 7, sp = tid & 7;
                const uint32_t* myrec = scratch + OFF_REC + (tm * 8 + r) * REC_CTA;
                uint4 v;
                uint2 ml;
                int it = 0;
#pragma unroll 1
                while (true) {
                    v = ld_poll4(myrec + (hh * 8 + sp) * 32 + dq * 4);
                    ml = ld_poll2(myrec + 512 + (hh * 8 + sp) * 8);
                    if (__all_sync(0xffffffffu, v.x && v.y && v.z && v.w && ml.x && ml.y)) break;
                    if (++it > SPIN_LIMIT) __trap();
                }
                st_zero4_if(tid < 16, g_q + ((r >> 2) * 2 + ab) * 2048 + ag * 256 + (r & 3) * 64 + tid * 4);
                const float m = decf(ml.x), l = decf(ml.y);
                float M = m;
#pragma unroll
                for (int x = 1; x <= 4; x <<= 1) M = fmaxf(M, __shfl_xor_sync(0xffffffffu, M, x));
                const float a = ex2(m - M);
                float L = a * l, o0 = a * decf(v.x), o1 = a * decf(v.y), o2 = a * decf(v.z), o3 = a * decf(v.w);
#pragma unroll
                for (int x = 1; x <= 4; x <<= 1) {
                    L += __shfl_xor_sync(0xffffffffu, L, x);
                    o0 += __shfl_xor_sync(0xffffffffu, o0, x);
                    o1 += __shfl_xor_sync(0xffffffffu, o1, x);
                    o2 += __shfl_xor_sync(0xffffffffu, o2, x);
                    o3 += __shfl_xor_sync(0xffffffffu, o3, x);
                }
                const float inv = __frcp_rn(L);
                const uint2 pk = make_uint2(pack_bf16(o0 * inv, o1 * inv), pack_bf16(o2 * inv, o3 * inv));
                if (sp == 0) *reinterpret_cast<uint2*>(smem + SM_OS + hh * 64 + dq * 8) = pk;
            }
            bar_consumers();
            ow = reinterpret_cast<const uint32_t*>(smem + SM_OS)[lane];
        } else {
            const uint32_t* mp = g_ml + lane * 4;
            const uint32_t* pp = g_p + w * 256 + (lane & 7) * 4;
            uint4 a, b, pv[8];
            {
                int it = 0;
#pragma unroll 1
                while (true) {
                    a = ld_poll4(mp);
                    b = ld_poll4(mp + 128);
                    bool ok = true;
#pragma unroll
                    for (int i = 0; i < 8; ++i) pv[i] = ld_poll4(pp + i * 32);
#pragma unroll
                    for (int i = 0; i < 8; ++i) ok = ok && pv[i].x && pv[i].y && pv[i].z && pv[i].w;
                    if (__all_sync(0xffffffffu, ok && a.x && a.y && a.z && a.w && b.x && b.y && b.z && b.w)) break;
                    if (++it > SPIN_LIMIT) __trap();
                }
            }
            float f[8][2];
            {
                const float ma0 = decf(a.x), ma1 = decf(a.z), mb0 = decf(b.x), mb1 = decf(b.z);
                float M0 = fmaxf(ma0, mb0), M1 = fmaxf(ma1, mb1);
#pragma unroll
                for (int x = 1; x <= 16; x <<= 1) {
                    M0 = fmaxf(M0, __shfl_xor_sync(0xffffffffu, M0, x));
                    M1 = fmaxf(M1, __shfl_xor_sync(0xffffffffu, M1, x));
                }
                const float fa0 = ex2(ma0 - M0), fa1 = ex2(ma1 - M1), fb0 = ex2(mb0 - M0), fb1 = ex2(mb1 - M1);
                float L0 = fmaf(fa0, decf(a.y), fb0 * decf(b.y)), L1 = fmaf(fa1, decf(a.w), fb1 * decf(b.w));
#pragma unroll
                for (int x = 1; x <= 16; x <<= 1) {
                    L0 += __shfl_xor_sync(0xffffffffu, L0, x);
                    L1 += __shfl_xor_sync(0xffffffffu, L1, x);
                }
                const float u0 = (w < 4 ? fa0 : fb0) * __frcp_rn(L0), u1 = (w < 4 ? fa1 : fb1) * __frcp_rn(L1);
#pragma unroll
                for (int ks = 0; ks < 8; ++ks) {
                    f[ks][0] = __shfl_sync(0xffffffffu, u0, (w & 3) * 8 + ks);
                    f[ks][1] = __shfl_sync(0xffffffffu, u1, (w & 3) * 8 + ks);
                }
            }
            float acc[8][2][4];
#pragma unroll
            for (int it = 0; it < 2; ++it) {
                const uint32_t slot = ring + s3 * (8 * SLOT);
                mbar_wait_warp(fullw + 64 * s3, ph);
                TSQ();
#pragma unroll
                for (int ks = 0; ks < 8; ++ks) {
#pragma unroll
                    for (int mt = 0; mt < 2; ++mt) {
                        uint32_t av[4];
                        ldsm4t(av, slot + ks * 1024 + voff[mt]);
                        if (it == 0) { acc[ks][mt][0] = 0.f; acc[ks][mt][1] = 0.f; acc[ks][mt][2] = 0.f; acc[ks][mt][3] = 0.f; }
                        mma16816(acc[ks][mt], av, ~(it ? pv[ks].z : pv[ks].x), ~(it ? pv[ks].w : pv[ks].y));
                    }
                }
                if (++s3 == 3) { s3 = 0; ph ^= 1; }
            }
            float o[2][4];
#pragma unroll
            for (int mt = 0; mt < 2; ++mt) {
#pragma unroll
                for (int c = 0; c < 4; ++c) {
                    float e = 0.f, d = 0.f;
#pragma unroll
                    for (int ks = 0; ks < 8; ks += 2) { e = fmaf(f[ks][c & 1], acc[ks][mt][c], e); d = fmaf(f[ks + 1][c & 1], acc[ks + 1][mt][c], d); }
                    o[mt][c] = e + d;
                }
            }
            TS(5);
            float* const orp = reinterpret_cast<float*>(smem + SM_OR);
            const float v0 = (t & 2) ? ((t & 1) ? o[1][2] : o[1][0]) : ((t & 1) ? o[0][2] : o[0][0]);
            const float v1 = (t & 2) ? ((t & 1) ? o[1][3] : o[1][1]) : ((t & 1) ? o[0][3] : o[0][1]);
            orp[w * 64 + 8 * t + g] = v0;
            orp[w * 64 + 32 + 8 * t + g] = v1;
            bar_consumers();
            float sx = 0.f, sy = 0.f;
#pragma unroll
            for (int i = 0; i < 8; ++i) {
                const float2 v = reinterpret_cast<const float2*>(orp + i * 64)[lane];
                sx += v.x; sy += v.y;
            }
            ow = pack_bf16(sx, sy);
            TS(6);
        }
        project(seg, ow, s3, ph);
        if (seg == 0) {
            bar_consumers();
            if (lane == 0) mbar_arrive(emptyw + 64 * s3);
            if (++s3 == 3) { s3 = 0; ph ^= 1; }
        }
    }
    TS(9);
    TSX(8);

    if (w < 2 && j < 112) {
        const int fb = j >= 56, cb = j - fb * 56;
        const uint32_t* src = g_outp + (w * 112 + j) * 512 + lane * 4;
        const int col = 4 * (lane & 1) + 2 * (lane >> 4) + ((lane >> 3) & 1);
        __nv_bfloat16* dst = outp + fb * 896 + w * 448 + cb * 8 + col;
        asm volatile("" : "+l"(dst));
        uint4 v[4];
        int it = 0;
#pragma unroll 1
        while (true) {
            bool all = true;
#pragma unroll
            for (int i = 0; i < 4; ++i) v[i] = ld_poll4(src + i * 128);
#pragma unroll
            for (int i = 0; i < 4; ++i) all = all && v[i].x && v[i].y && v[i].z && v[i].w;
            if (__all_sync(0xffffffffu, all)) break;
            if (++it > SPIN_LIMIT) __trap();
            POLL_SLEEP(NS_FIN);
        }
        float a0 = 0.f, a1 = 0.f, a2 = 0.f, a3 = 0.f;
#pragma unroll
        for (int i = 0; i < 4; ++i) { a0 += decf(v[i].x); a1 += decf(v[i].y); a2 += decf(v[i].z); a3 += decf(v[i].w); }
        const bool u16 = lane & 16, u8 = lane & 8;
        float h0 = (u16 ? a2 : a0) + __shfl_xor_sync(0xffffffffu, u16 ? a0 : a2, 16);
        float h1 = (u16 ? a3 : a1) + __shfl_xor_sync(0xffffffffu, u16 ? a1 : a3, 16);
        float z = (u8 ? h1 : h0) + __shfl_xor_sync(0xffffffffu, u8 ? h0 : h1, 8);
        z += __shfl_xor_sync(0xffffffffu, z, 4);
        z += __shfl_xor_sync(0xffffffffu, z, 2);
        if ((lane & 6) == 0) *dst = __float2bfloat16_rn(z);
    }
    TS(10);
}

typedef CUresult (*EncodeTiledFn)(CUtensorMap*, CUtensorMapDataType, cuuint32_t, void*, const cuuint64_t*,
                                  const cuuint64_t*, const cuuint32_t*, const cuuint32_t*, CUtensorMapInterleave,
                                  CUtensorMapSwizzle, CUtensorMapL2promotion, CUtensorMapFloatOOBfill);

}

extern "C" void kernel_launch(void* const* d_in, const int* in_sizes, int n_in, void* d_out, int out_size) {
    (void)in_sizes; (void)n_in; (void)out_size;
    static EncodeTiledFn encode = nullptr;
    static uint32_t* scratch = nullptr;
    if (!encode) {
        void* fn = nullptr;
        cudaDriverEntryPointQueryResult qr;
        cudaGetDriverEntryPoint("cuTensorMapEncodeTiled", &fn, cudaEnableDefault, &qr);
        encode = (EncodeTiledFn)fn;
        void* sp = nullptr;
        cudaGetSymbolAddress(&sp, g_scratch);
        scratch = (uint32_t*)sp;
        cudaFuncSetAttribute(fused_decode_kernel, cudaFuncAttributeMaxDynamicSharedMemorySize, SM_TOTAL);
    }
    Maps P;
    for (int p = 0; p < 2; ++p) {
        const cuuint32_t es[3] = {1, 1, 1};
        {
            const cuuint64_t dims[3] = {64, 448, 64};
            const cuuint64_t strides[2] = {8192, 128};
            const cuuint32_t box[3] = {64, 56, 1};
            encode(&P.m[p], CU_TENSOR_MAP_DATA_TYPE_BFLOAT16, 3, d_in[5 * p + 3], dims, strides, box, es,
                   CU_TENSOR_MAP_INTERLEAVE_NONE, CU_TENSOR_MAP_SWIZZLE_NONE, CU_TENSOR_MAP_L2_PROMOTION_NONE,
                   CU_TENSOR_MAP_FLOAT_OOB_FILL_NONE);
        }
        {
            const cuuint64_t dims[3] = {64, 131072, 4};
            const cuuint64_t strides[2] = {512, 128};
            const cuuint32_t box[3] = {64, 16, 4};
            encode(&P.m[2 + 2 * p], CU_TENSOR_MAP_DATA_TYPE_BFLOAT16, 3, d_in[5 * p + 1], dims, strides, box, es,
                   CU_TENSOR_MAP_INTERLEAVE_NONE, CU_TENSOR_MAP_SWIZZLE_128B, CU_TENSOR_MAP_L2_PROMOTION_NONE,
                   CU_TENSOR_MAP_FLOAT_OOB_FILL_NONE);
        }
        if (p == 0) {
            const cuuint64_t dims[3] = {64, 131072, 4};
            const cuuint64_t strides[2] = {512, 128};
            const cuuint32_t box[3] = {64, 16, 4};
            encode(&P.m[3], CU_TENSOR_MAP_DATA_TYPE_BFLOAT16, 3, d_in[2], dims, strides, box, es,
                   CU_TENSOR_MAP_INTERLEAVE_NONE, CU_TENSOR_MAP_SWIZZLE_128B, CU_TENSOR_MAP_L2_PROMOTION_NONE,
                   CU_TENSOR_MAP_FLOAT_OOB_FILL_NONE);
        } else {
            const cuuint64_t dims[3] = {256, 131072, 1};
            const cuuint64_t strides[2] = {512, 512ull * 131072};
            const cuuint32_t box[3] = {32, 128, 1};
            encode(&P.m[5], CU_TENSOR_MAP_DATA_TYPE_BFLOAT16, 3, d_in[7], dims, strides, box, es,
                   CU_TENSOR_MAP_INTERLEAVE_NONE, CU_TENSOR_MAP_SWIZZLE_64B, V_PROMO,
                   CU_TENSOR_MAP_FLOAT_OOB_FILL_NONE);
        }
        const cuuint64_t dims[3] = {64, 4096, 7};
        const cuuint64_t strides[2] = {896, 128};
        const cuuint32_t box[3] = {64, 8, 7};
        encode(&P.m[6 + p], CU_TENSOR_MAP_DATA_TYPE_BFLOAT16, 3, d_in[5 * p + 4], dims, strides, box, es,
               CU_TENSOR_MAP_INTERLEAVE_NONE, CU_TENSOR_MAP_SWIZZLE_128B, CU_TENSOR_MAP_L2_PROMOTION_NONE,
               CU_TENSOR_MAP_FLOAT_OOB_FILL_NONE);
    }
    fused_decode_kernel<<<NCTA, NTHR, SM_TOTAL, cudaStreamPerThread>>>(d_in[0], d_in[5], scratch, (__nv_bfloat16*)d_out, P);
}
```

```cpp
#include <cuda_runtime.h>
#include <cuda.h>
#include <cuda_bf16.h>
#include <stdint.h>

#define W_MAIN 9
#define W_WO 7
#define W_T18 W_MAIN
#define W_T19 W_MAIN

#define W_MIN 3
#define W_MAX 12
#define PACE_MODE 3
#define PACE_INC 2
#define PACE_RND 0
#define PACE_Q0 1
#define PACE_SH 2
#define NS_PACE 200
#define WO_POS 0
#define WO_WT 7
#define W_HI_WO 14
#define W_LO 3
#define W_HI 12
#define PACE_OFF 0
#define PACE_AGE 0.5f
#define WO_BURST 8
#define RHO0 3.65f
#define RHO_A 0.25f

#define FIN_ATOM 1
#define ACC_STRIDE 32
#define ATOM_W 3
#define PROJ_PAIR 1
#define WO_ADJ 0
#define WOA_ADJ 0
#define V_ADJ 0
#define MAIN_ADJ 0
#define NO_CLEAR 0
#define PACE_ALPHA 100
#define EVICT_FIRST 1
#define V_PROMO CU_TENSOR_MAP_L2_PROMOTION_L2_128B
#define ORDER 3
#define W_V W_MAIN
#define W_WOA W_MAIN
#define NS_Q 40
#define NS_REC 40
#define NS_FIN 0
#define POLL_SLEEP(ns) do { if ((ns) > 0) __nanosleep(ns); } while (0)

#define TRAPX(code) __trap();
#define ABORTED false
#define MARK(loc) do { } while (0)
namespace {

constexpr int NCTA = 128;
constexpr int NTHR = 320;
constexpr int SLOT = 8192;
constexpr int SM_RED = 24 * SLOT;
constexpr int SM_SC = SM_RED + 16384;
constexpr int SM_OR = SM_SC + 2048;
constexpr int SM_QS = SM_OR + 2048;
constexpr int SM_ML = SM_QS + 2048;
constexpr int SM_OS = SM_ML + 128;
constexpr int SM_BAR = SM_OS + 128;
constexpr int SM_FLAG = SM_BAR + 384;
constexpr int SM_TOTAL = SM_FLAG + 32 + 1024;
constexpr int SPIN_LIMIT = 1 << 20;
constexpr int NQ = 22;
constexpr int Q_WOA = 18, Q_WOB = 21 - WO_POS;

constexpr int Q_WORDS = 2 * 2 * 2048;
constexpr int P_WORDS = 16 * 2048;
constexpr int ML_WORDS = 16 * 64 * 4;
constexpr int REC_CTA = 640;
constexpr int REC_WORDS = NCTA * REC_CTA;
constexpr int OUTP_WORDS = 2 * 2 * 56 * 64 * 8;
constexpr int OFF_P = Q_WORDS, OFF_ML = OFF_P + P_WORDS, OFF_REC = OFF_ML + ML_WORDS, OFF_OUTP = OFF_REC + REC_WORDS;
constexpr int OFF_PACE = OFF_OUTP + OUTP_WORDS;
constexpr int PACE_WORDS = 64;

struct alignas(64) Maps {
    CUtensorMap m[8];
};

constexpr int SCRATCH_WORDS = OFF_PACE + PACE_WORDS;
__device__ __align__(128) uint32_t g_scratch[SCRATCH_WORDS];

#define TSX(i) do { } while (0)
#define TS(i) do { } while (0)
#define TSP(i) do { } while (0)
#define TSQ() do { } while (0)

__device__ __forceinline__ uint32_t enc(uint32_t bits) { return max(~bits, 1u); }
__device__ __forceinline__ uint32_t encf(float f) { return enc(__float_as_uint(f)); }
__device__ __forceinline__ float decf(uint32_t w) { return __uint_as_float(~w); }

__device__ __forceinline__ uint32_t ld_poll(const uint32_t* p) {
    uint32_t v;
    asm volatile("ld.relaxed.gpu.global.u32 %0, [%1];" : "=r"(v) : "l"(p) : "memory");
    return v;
}
__device__ __forceinline__ uint2 ld_poll2(const uint32_t* p) {
    uint2 v;
    asm volatile("ld.relaxed.gpu.global.v2.u32 {%0,%1}, [%2];" : "=r"(v.x), "=r"(v.y) : "l"(p) : "memory");
    return v;
}
__device__ __forceinline__ uint4 ld_poll4(const uint32_t* p) {
    uint4 v;
    asm volatile("ld.relaxed.gpu.global.v4.u32 {%0,%1,%2,%3}, [%4];"
                 : "=r"(v.x), "=r"(v.y), "=r"(v.z), "=r"(v.w) : "l"(p) : "memory");
    return v;
}
__device__ __forceinline__ void st_zero4_if(bool pred, uint32_t* p) {
    asm volatile("{\n.reg .pred p;\nsetp.ne.u32 p, %2, 0;\n@p st.relaxed.gpu.global.v4.u32 [%0], {%1,%1,%1,%1};\n}"
                 ::"l"(p), "r"(0u), "r"((uint32_t)pred) : "memory");
}
__device__ __forceinline__ void st_pub(uint32_t* p, uint32_t v) {
    asm volatile("st.relaxed.gpu.global.u32 [%0], %1;" ::"l"(p), "r"(v) : "memory");
}
__device__ __forceinline__ void st_pub_if(bool pred, uint32_t* p, uint32_t v) {
    asm volatile("{\n.reg .pred p;\nsetp.ne.u32 p, %2, 0;\n@p st.relaxed.gpu.global.u32 [%0], %1;\n}"
                 ::"l"(p), "r"(v), "r"((uint32_t)pred) : "memory");
}
__device__ __forceinline__ void st_pub2_if(bool pred, uint32_t* p, uint32_t a, uint32_t b) {
    asm volatile("{\n.reg .pred p;\nsetp.ne.u32 p, %3, 0;\n@p st.relaxed.gpu.global.v2.u32 [%0], {%1,%2};\n}"
                 ::"l"(p), "r"(a), "r"(b), "r"((uint32_t)pred) : "memory");
}
__device__ __forceinline__ void st_pub4_if(bool pred, uint32_t* p, uint32_t a, uint32_t b, uint32_t c, uint32_t d) {
    asm volatile("{\n.reg .pred p;\nsetp.ne.u32 p, %5, 0;\n@p st.relaxed.gpu.global.v4.u32 [%0], {%1,%2,%3,%4};\n}"
                 ::"l"(p), "r"(a), "r"(b), "r"(c), "r"(d), "r"((uint32_t)pred) : "memory");
}
__device__ __forceinline__ void st_zero4(uint32_t* p) {
    asm volatile("st.relaxed.gpu.global.v4.u32 [%0], {%1,%1,%1,%1};" ::"l"(p), "r"(0u) : "memory");
}
__device__ __forceinline__ uint32_t ldg_u32(const void* p) {
    uint32_t v;
    asm volatile("ld.global.u32 %0, [%1];" : "=r"(v) : "l"(p) : "memory");
    return v;
}

__device__ __forceinline__ void mbar_init(uint32_t bar, uint32_t cnt) {
    asm volatile("mbarrier.init.shared::cta.b64 [%0], %1;" ::"r"(bar), "r"(cnt) : "memory");
}
__device__ __forceinline__ void mbar_expect_tx(uint32_t bar, uint32_t bytes) {
    asm volatile("mbarrier.arrive.expect_tx.shared::cta.b64 _, [%0], %1;" ::"r"(bar), "r"(bytes) : "memory");
}
__device__ __forceinline__ void mbar_arrive(uint32_t bar) {
    asm volatile("mbarrier.arrive.shared::cta.b64 _, [%0];" ::"r"(bar) : "memory");
}
__device__ __forceinline__ bool mbar_try(uint32_t bar, uint32_t parity) {
    uint32_t ok;
    asm volatile("{\n.reg .pred p;\nmbarrier.try_wait.parity.shared::cta.b64 p, [%1], %2;\nselp.u32 %0, 1, 0, p;\n}"
                 : "=r"(ok) : "r"(bar), "r"(parity) : "memory");
    return ok;
}
__device__ __forceinline__ bool mbar_test(uint32_t bar, uint32_t parity) {
    uint32_t ok;
    asm volatile("{\n.reg .pred p;\nmbarrier.test_wait.parity.shared::cta.b64 p, [%1], %2;\nselp.u32 %0, 1, 0, p;\n}"
                 : "=r"(ok) : "r"(bar), "r"(parity) : "memory");
    return ok;
}
__device__ __forceinline__ void mbar_wait1(uint32_t bar, uint32_t parity) {
    int it = 0;
#pragma unroll 1
    while (!mbar_try(bar, parity)) { if (++it > SPIN_LIMIT || ABORTED) TRAPX(1) }
}
__device__ __forceinline__ void mbar_wait_warp(uint32_t bar, uint32_t parity) {
    int it = 0;
#pragma unroll 1
    while (!__all_sync(0xffffffffu, mbar_try(bar, parity))) { if (++it > SPIN_LIMIT || ABORTED) TRAPX(2) }
}
__device__ __forceinline__ void tma3d(uint32_t dst, const CUtensorMap* m, int col, int row, int chunk, uint32_t bar, uint64_t pol) {
    asm volatile("cp.async.bulk.tensor.3d.shared::cluster.global.mbarrier::complete_tx::bytes.L2::cache_hint"
                 " [%0], [%1, {%3, %4, %5}], [%2], %6;"
                 ::"r"(dst), "l"(m), "r"(bar), "r"(col), "r"(row), "r"(chunk), "l"(pol) : "memory");
}
__device__ __forceinline__ void tma3d_elect(uint32_t dst, const CUtensorMap* m, int col, int row, uint32_t bar, uint32_t bytes, uint64_t pol) {
    asm volatile("{\n.reg .pred p;\nelect.sync _|p, 0xffffffff;\n"
                 "@p mbarrier.arrive.expect_tx.shared::cta.b64 _, [%2], %6;\n"
                 "@p cp.async.bulk.tensor.3d.shared::cluster.global.mbarrier::complete_tx::bytes.L2::cache_hint"
                 " [%0], [%1, {%3, %4, %5}], [%2], %7;\n}"
                 ::"r"(dst), "l"(m), "r"(bar), "r"(col), "r"(row), "r"(0), "r"(bytes), "l"(pol) : "memory");
}
__device__ __forceinline__ uint64_t stream_policy() {
    uint64_t pol;
    asm("createpolicy.fractional.L2::evict_first.b64 %0, 1.0;" : "=l"(pol));
    return pol;
}
__device__ __forceinline__ void bar_consumers() { asm volatile("bar.sync 1, 256;" ::: "memory"); }

__device__ __forceinline__ void ldsm4(uint32_t (&a)[4], uint32_t addr) {
    asm volatile("ldmatrix.sync.aligned.m8n8.x4.shared.b16 {%0,%1,%2,%3}, [%4];"
                 : "=r"(a[0]), "=r"(a[1]), "=r"(a[2]), "=r"(a[3]) : "r"(addr) : "memory");
}
__device__ __forceinline__ void ldsm4t(uint32_t (&a)[4], uint32_t addr) {
    asm volatile("ldmatrix.sync.aligned.m8n8.x4.trans.shared.b16 {%0,%1,%2,%3}, [%4];"
                 : "=r"(a[0]), "=r"(a[1]), "=r"(a[2]), "=r"(a[3]) : "r"(addr) : "memory");
}
__device__ __forceinline__ void ldsm2t(uint32_t (&a)[2], uint32_t addr) {
    asm volatile("ldmatrix.sync.aligned.m8n8.x2.trans.shared.b16 {%0,%1}, [%2];"
                 : "=r"(a[0]), "=r"(a[1]) : "r"(addr) : "memory");
}
__device__ __forceinline__ void mma16816(float (&c)[4], const uint32_t (&a)[4], uint32_t b0, uint32_t b1) {
    asm("mma.sync.aligned.m16n8k16.row.col.f32.bf16.bf16.f32 {%0,%1,%2,%3}, {%4,%5,%6,%7}, {%8,%9}, {%0,%1,%2,%3};"
        : "+f"(c[0]), "+f"(c[1]), "+f"(c[2]), "+f"(c[3])
        : "r"(a[0]), "r"(a[1]), "r"(a[2]), "r"(a[3]), "r"(b0), "r"(b1));
}
__device__ __forceinline__ void mma1688(float (&c)[4], uint32_t a0, uint32_t b0) {
    asm("mma.sync.aligned.m16n8k8.row.col.f32.bf16.bf16.f32 {%0,%1,%2,%3}, {%4,%5}, {%6}, {%0,%1,%2,%3};"
        : "+f"(c[0]), "+f"(c[1]), "+f"(c[2]), "+f"(c[3]) : "r"(a0), "r"(0u), "r"(b0));
}
__device__ __forceinline__ uint32_t movtrans(uint32_t a) {
    uint32_t d;
    asm volatile("movmatrix.sync.aligned.m8n8.trans.b16 %0, %1;" : "=r"(d) : "r"(a));
    return d;
}
__device__ __forceinline__ float ex2(float x) {
    float y;
    asm("ex2.approx.ftz.f32 %0, %1;" : "=f"(y) : "f"(x));
    return y;
}
__device__ __forceinline__ uint32_t pack_bf16(float lo, float hi) {
    uint32_t d;
    asm("cvt.rn.bf16x2.f32 %0, %1, %2;" : "=r"(d) : "f"(hi), "f"(lo));
    return d;
}
__device__ __forceinline__ float bf_lo(uint32_t w) { return __uint_as_float(w << 16); }
__device__ __forceinline__ float bf_hi(uint32_t w) { return __uint_as_float(w & 0xffff0000u); }

constexpr float SCALE_LOG2 = 1.4426950408889634f / 16.0f;

__global__ void __launch_bounds__(NTHR, 1)
fused_decode_kernel(const void* __restrict__ xA, const void* __restrict__ xB, uint32_t* scratch, __nv_bfloat16* outp,
                    const __grid_constant__ Maps P) {
    extern __shared__ uint8_t smem_raw[];
    const int tid = threadIdx.x, w = tid >> 5, lane = tid & 31;
    const int j = blockIdx.x;
    const int op = j >> 6, jj = j & 63;
    const int r = (j & 1) | ((j >> 1) & 6), ab = (j >> 1) & 1, ag = j >> 4;
    const int tm = ab * 8 + ag;
    const uint32_t sraw = (uint32_t)__cvta_generic_to_shared(smem_raw);
    uint32_t sbase = (sraw + 1023u) & ~1023u;
    uint8_t* smem = smem_raw + (sbase - sraw);
    asm volatile("" : "+r"(sbase));
    const uint32_t full0 = sbase + SM_BAR, empty0 = full0 + 24 * 8;
    TS(0);

    const uint64_t pol = stream_policy();
    if (tid == 256) {
        asm volatile("prefetch.tensormap [%0];" ::"l"(&P.m[op]) : "memory");
#pragma unroll
        for (int s = 0; s < 8; ++s) mbar_init(full0 + 8 * s, 1);
        asm volatile("fence.mbarrier_init.release.cluster;" ::: "memory");
        TSP(15);
#pragma unroll 1
        for (int cw = 0; cw < 8; ++cw) {
            mbar_expect_tx(full0 + 8 * cw, 7168);
            tma3d(sbase + cw * SLOT, &P.m[op], 0, cw * 56, jj, full0 + 8 * cw, pol);
        }
    }
    if (tid == 0) {
#pragma unroll
        for (int s = 8; s < 48; ++s) mbar_init(full0 + 8 * s, 1);
        asm volatile("fence.mbarrier_init.release.cluster;" ::: "memory");
    }
    if (w == 8) {
        if (lane >= 2 && lane < 8) asm volatile("prefetch.tensormap [%0];" ::"l"(&P.m[lane]) : "memory");
        __syncwarp();
        asm volatile("bar.sync 2, 320;" ::: "memory");
        if (lane == 0) TSP(14);
        const int rowA = tm * 8192, rowB = rowA + 6144;
        int sl = 8;
        uint32_t ph = 0;
        int kw = 8 * 16;
        uint32_t myop = (1u << 10) | 16u;
        int spin = 0;
        int q = 0, cw = 0;
        const CUtensorMap* map;
        int row, rstep, col, Wb, whi, wt, lead;
        uint32_t bytes;
        bool iswo;
        auto setup = [&]() {
            rstep = 16; col = 0; Wb = W_V; bytes = SLOT; iswo = false; wt = 16; whi = W_HI;
            if (q < 16) { map = &P.m[2 + (q & 1)]; row = rowA + (q >> 1) * 1024 + r * 128; Wb = W_MAIN; }
            else if (q < 18) { map = &P.m[4]; row = rowB + r * 256 + (q - 16) * 128; Wb = W_MAIN; }
            else if (q == Q_WOB || q == Q_WOA) {
                map = &P.m[q == Q_WOB ? 7 : 6]; row = ag * 512 + r * 32; rstep = 8; bytes = 7168;
                Wb = q == Q_WOB ? W_WO : W_WOA; iswo = true; wt = WO_WT; whi = W_HI_WO;
            } else { map = &P.m[5]; row = rowB + (q - Q_WOA - 1 - (q > Q_WOB)) * 128; rstep = 256; col = r * 32; }
            lead = 16 * Wb + (q < 18 ? MAIN_ADJ : q == Q_WOB ? WO_ADJ : q == Q_WOA ? WOA_ADJ : V_ADJ);
        };
        setup();
#pragma unroll 1
        while (true) {
            MARK(1);
            int s2 = sl + lane - 24;
            uint32_t par = ph ^ 1;
            if (s2 >= 24) { s2 -= 24; par = ph; }
            const bool isf = lane < 24;
            const bool ok = mbar_test(isf ? full0 + 8 * lane : empty0 + 8 * s2, isf ? (lane < sl ? ph : ph ^ 1) : par);
            MARK(2);
            uint32_t c0, c1, c2, c3, now;
            asm volatile("ld.volatile.shared.v4.u32 {%0,%1,%2,%3}, [%4];"
                         : "=r"(c0), "=r"(c1), "=r"(c2), "=r"(c3) : "r"(sbase + SM_FLAG + 16) : "memory");
            asm volatile("mov.u32 %0, %%clock;" : "=r"(now));
            const int e0 = (int)(fmaf((float)min((int)(now - c1), 3500), __uint_as_float(c2), __uint_as_float(c0)) * (1.0f / NCTA));
            const uint32_t e1 = (lane == 24 && c3) ? (uint32_t)(min(max(e0, 0), 65000) + 1) << 16 : 0u;
            uint32_t fmask = __ballot_sync(0xffffffffu, ok) >> 24;
            const uint32_t fl = __reduce_add_sync(0xffffffffu, (isf && !ok) ? myop : e1);
            int infl = (fl >> 10) & 63;
            const int est = (int)(fl >> 16) - 1 + PACE_OFF;
            MARK(3);
            if (lane == 0) asm volatile("st.volatile.shared.s32 [%0], %1;" ::"r"(sbase + SM_FLAG + 8), "r"(kw - (int)(fl & 1023u)) : "memory");
            if (++spin > SPIN_LIMIT || ABORTED) {
                TRAPX(3)
            }
#pragma unroll 1
            while (fmask & 1) {
                const bool go = (iswo && (cw & (WO_BURST - 1)) != 0) || infl < W_LO ||
                                (infl < whi && (fl >> 16 ? kw - lead <= est : infl < Wb));
                if (!go) break;
                MARK(4);
                tma3d_elect(sbase + sl * SLOT, map, col, row, full0 + 8 * sl, bytes, pol);
                MARK(5);
                if (lane == sl) myop = (1u << 10) | wt;
                spin = 0;
                ++infl;
                kw += wt;
                fmask >>= 1;
                row += rstep;
                if (rstep == 8 && cw == 3) row += 224;
                if (++sl == 24) { sl = 0; ph ^= 1; }
                if (++cw == 8) {
                    cw = 0;
                    if (++q == NQ) break;
                    setup();
                }
            }
            if (q == NQ) break;
        }
        if (lane == 0) asm volatile("st.volatile.shared.s32 [%0], %1;" ::"r"(sbase + SM_FLAG + 4), "r"(1) : "memory");
        return;
    }

    if (w == 9) {
        uint32_t* const pB = scratch + OFF_P + tm * 2048 + r * 256;
        uint32_t* const ml = scratch + OFF_ML + tm * 256 + r * 32;
        uint32_t* const rec_in = scratch + OFF_REC + (tm * 8 + r) * REC_CTA;
        uint32_t* const outp_in = scratch + OFF_OUTP + j * 512;
        uint32_t* const cleared = scratch + OFF_PACE + 32;
        if (lane < 2) asm volatile("st.shared.v4.u32 [%0], {%1, %1, %1, %1};" ::"r"(sbase + SM_FLAG + 16 * lane), "r"(0) : "memory");
        __syncwarp();
        asm volatile("bar.arrive 2, 320;" ::: "memory");
#pragma unroll
        for (int i = 0; i < 2; ++i) st_zero4(pB + i * 128 + lane * 4);
        st_zero4_if(lane < 8, ml + (lane & 7) * 4);
#pragma unroll
        for (int i = 0; i < 5; ++i) st_zero4(rec_in + i * 128 + lane * 4);
        {
            const int a = j * 5 + (lane >> 1);
            st_zero4_if(lane < 10, scratch + OFF_OUTP + (a >= 320 ? 112 * 512 + (a - 320) * ACC_STRIDE : a * ACC_STRIDE) + (lane & 1) * 4);
        }
        uint32_t* const prog = scratch + OFF_PACE;
        if (j == 0 && lane == 0) st_pub(prog, 0);
        __syncwarp();
        if (lane == 0) {
            uint32_t c;
            asm volatile("atom.release.gpu.global.add.u32 %0, [%1], 1;" : "=r"(c) : "l"(cleared) : "memory");
            const uint32_t target = (c & ~(uint32_t)(NCTA - 1)) + NCTA;
            int it = 0;
#pragma unroll 1
            while (true) {
                asm volatile("ld.acquire.gpu.global.u32 %0, [%1];" : "=r"(c) : "l"(cleared) : "memory");
                if ((int32_t)(c - target) >= 0) break;
                if (++it > SPIN_LIMIT || ABORTED) TRAPX(4)
                __nanosleep(200);
            }
        }
        __syncwarp();
        asm volatile("bar.arrive 3, 288;" ::: "memory");
        if (lane == 0) {
            int last = 0, psum = 0;
            uint32_t pts = 0;
            float rho = RHO0;
#pragma unroll 1
            for (int it = 0; it < 4096; ++it) {
                int own, done, sum;
                uint32_t t0, t1;
                asm volatile("ld.volatile.shared.s32 %0, [%1];" : "=r"(done) : "r"(sbase + SM_FLAG + 4) : "memory");
                if (done) break;
                asm volatile("ld.volatile.shared.s32 %0, [%1];" : "=r"(own) : "r"(sbase + SM_FLAG + 8) : "memory");
                asm volatile("mov.u32 %0, %%clock;" : "=r"(t0));
                asm volatile("atom.relaxed.gpu.global.add.s32 %0, [%1], %2;" : "=r"(sum) : "l"(prog), "r"(own - last) : "memory");
                asm volatile("{\n.reg .u32 t;\nadd.u32 t, %1, 0;\nmov.u32 %0, %%clock;\n}" : "=r"(t1) : "r"(sum) : "memory");
                sum += own - last;
                last = own;
                const uint32_t ts = t0 + ((t1 - t0) >> 1);
                const float per = (float)(int)(ts - pts);
                if (it >= 3) rho += ((float)(sum - psum) / per - rho) * RHO_A;
                float cur = fmaf(rho * PACE_AGE, per + (float)(int)(t1 - t0), (float)sum);
                psum = sum; pts = ts;
                if (it >= 2)
                    asm volatile("st.volatile.shared.v4.u32 [%0], {%1,%2,%3,%4};"
                                 ::"r"(sbase + SM_FLAG + 16), "r"(__float_as_uint(cur)), "r"(ts), "r"(__float_as_uint(rho)), "r"(1) : "memory");
                __nanosleep(NS_PACE);
            }
        }
        return;
    }

    uint32_t* const g_q = scratch;
    uint32_t* const g_outp = scratch + OFF_OUTP;
    const int g = lane >> 2, t = lane & 3;
    const int rg = w * 4 + (lane >> 3);
    uint32_t xa[7], xb[7];
    {
        const uint32_t* xp = (const uint32_t*)(op ? xB : xA) + rg * 7;
#pragma unroll
        for (int i = 0; i < 7; ++i) { xa[i] = ldg_u32(xp + i); xb[i] = ldg_u32(xp + 224 + i); }
    }
    asm volatile("bar.sync 2, 320;" ::: "memory");
    uint4 wv[14];
    mbar_wait_warp(full0 + 8 * w, 0);
    TS(3);
    {
        const uint4* wq = reinterpret_cast<const uint4*>(smem + w * SLOT) + (lane >> 3) * (14 * 8) + (lane & 7);
#pragma unroll
        for (int i = 0; i < 14; ++i) wv[i] = wq[i * 8];
    }

    {
        float acc[2][8];
#pragma unroll
        for (int c = 0; c < 8; ++c) { acc[0][c] = 0.f; acc[1][c] = 0.f; }
#pragma unroll
        for (int i = 0; i < 14; ++i) {
            const float x0 = (i & 1) ? bf_hi(xa[i >> 1]) : bf_lo(xa[i >> 1]);
            const float x1 = (i & 1) ? bf_hi(xb[i >> 1]) : bf_lo(xb[i >> 1]);
            const uint32_t ww[4] = {wv[i].x, wv[i].y, wv[i].z, wv[i].w};
#pragma unroll
            for (int c = 0; c < 4; ++c) {
                const float a = bf_lo(ww[c]), b = bf_hi(ww[c]);
                acc[0][2 * c] = fmaf(x0, a, acc[0][2 * c]); acc[0][2 * c + 1] = fmaf(x0, b, acc[0][2 * c + 1]);
                acc[1][2 * c] = fmaf(x1, a, acc[1][2 * c]); acc[1][2 * c + 1] = fmaf(x1, b, acc[1][2 * c + 1]);
            }
        }
        __syncwarp();
        if (lane == 0) mbar_arrive(empty0 + 8 * w);
        const bool u16 = lane & 16, u8 = lane & 8;
        float h[8];
#pragma unroll
        for (int c = 0; c < 8; ++c) {
            const float send = u16 ? acc[0][c] : acc[1][c], keep = u16 ? acc[1][c] : acc[0][c];
            h[c] = keep + __shfl_xor_sync(0xffffffffu, send, 16);
        }
        float q4[4];
#pragma unroll
        for (int c = 0; c < 4; ++c) {
            const float send = u8 ? h[c] : h[4 + c], keep = u8 ? h[4 + c] : h[c];
            q4[c] = keep + __shfl_xor_sync(0xffffffffu, send, 8);
        }
        float* qred = reinterpret_cast<float*>(smem + SM_RED);
        *reinterpret_cast<float4*>(qred + w * 128 + (lane >> 4) * 64 + (lane & 7) * 8 + ((lane >> 3) & 1) * 4) =
            make_float4(q4[0], q4[1], q4[2], q4[3]);
        bar_consumers();
        if (tid < 64) {
            float s0 = 0.f, s1 = 0.f;
#pragma unroll
            for (int i = 0; i < 8; ++i) {
                const float2 v = reinterpret_cast<const float2*>(qred + i * 128)[tid];
                s0 += v.x; s1 += v.y;
            }
            st_pub(g_q + (op * 2 + (tid >> 5)) * 2048 + jj * 32 + (tid & 31), enc(pack_bf16(s0, s1)));
        }
    }
    TS(1);

    uint32_t* qs = reinterpret_cast<uint32_t*>(smem + SM_QS);
    {
        const uint32_t* qB = g_q + (2 + ab) * 2048 + ag * 256 + tid;
        const uint32_t* qA = g_q + ab * 2048 + ag * 256 + tid;
        uint32_t a = 0, b = 0;
        int it = 0;
#pragma unroll 1
        while (true) {
            if (!b) b = ld_poll(qB);
            if (!a) a = ld_poll(qA);
            if (__all_sync(0xffffffffu, a && b)) break;
            if (++it > SPIN_LIMIT || ABORTED) TRAPX(5)
            POLL_SLEEP(NS_Q);
        }
        qs[tid] = ~b;
        qs[256 + tid] = ~a;
        TSX(0);
        bar_consumers();
    }
    TS(2);
    TSX(1);

    const uint32_t ring = sbase + w * SLOT;
    const uint32_t fullw = full0 + 8 * w, emptyw = empty0 + 8 * w;
    int s3 = 1;
    uint32_t ph = 0;
    uint32_t koff[4];
    {
        const int kkey = (lane & 7) + 8 * ((lane >> 3) & 1), khi = lane >> 4;
#pragma unroll
        for (int c = 0; c < 4; ++c) koff[c] = kkey * 128 + (((2 * c + khi) ^ (lane & 7)) << 4);
    }
    {
        uint32_t voff[4];
        const int vkey = (lane & 7) + 8 * (lane >> 4), vhi = (lane >> 3) & 1;
#pragma unroll
        for (int c = 0; c < 4; ++c) voff[c] = vkey * 128 + (((2 * c + vhi) ^ (lane & 7)) << 4);
        float o[16][4];
        uint32_t qf[32];
#pragma unroll
        for (int i = 0; i < 16; ++i) { o[i][0] = 0.f; o[i][1] = 0.f; o[i][2] = 0.f; o[i][3] = 0.f; }
        float m0 = -INFINITY, m1 = -INFINITY, l0 = 0.f, l1 = 0.f;
#pragma unroll
        for (int ks = 0; ks < 16; ++ks) {
            const uint32_t a = qs[256 + (g & 1) * 128 + ks * 8 + t], b = qs[256 + (g & 1) * 128 + ks * 8 + 4 + t];
            qf[2 * ks] = g < 2 ? a : 0u; qf[2 * ks + 1] = g < 2 ? b : 0u;
        }
#pragma unroll 1
        for (int it = 0; it < 8; ++it) {
            float sc[4];
            {
                const uint32_t slot = ring + s3 * (8 * SLOT);
                mbar_wait_warp(fullw + 64 * s3, ph);
                TSQ();
                float acc[4][4];
#pragma unroll
                for (int c = 0; c < 4; ++c) { acc[c][0] = 0.f; acc[c][1] = 0.f; acc[c][2] = 0.f; acc[c][3] = 0.f; }
#pragma unroll
                for (int ks = 0; ks < 16; ++ks) {
                    uint32_t a[4];
                    ldsm4(a, slot + (ks >> 2) * 2048 + koff[ks & 3]);
                    mma16816(acc[ks & 3], a, qf[2 * ks], qf[2 * ks + 1]);
                }
                __syncwarp();
                if (lane == 0) mbar_arrive(emptyw + 64 * s3);
                if (++s3 == 3) { s3 = 0; ph ^= 1; }
#pragma unroll
                for (int i = 0; i < 4; ++i) sc[i] = (acc[0][i] + acc[1][i]) + (acc[2][i] + acc[3][i]);
            }
            float mx0 = fmaxf(sc[0], sc[2]), mx1 = fmaxf(sc[1], sc[3]);
#pragma unroll
            for (int x = 4; x <= 16; x <<= 1) {
                mx0 = fmaxf(mx0, __shfl_xor_sync(0xffffffffu, mx0, x));
                mx1 = fmaxf(mx1, __shfl_xor_sync(0xffffffffu, mx1, x));
            }
            const float mn0 = fmaxf(m0, mx0 * SCALE_LOG2), mn1 = fmaxf(m1, mx1 * SCALE_LOG2);
            const float al0 = ex2(m0 - mn0), al1 = ex2(m1 - mn1);
            const float p0 = ex2(fmaf(sc[0], SCALE_LOG2, -mn0)), p1 = ex2(fmaf(sc[1], SCALE_LOG2, -mn1));
            const float p2 = ex2(fmaf(sc[2], SCALE_LOG2, -mn0)), p3 = ex2(fmaf(sc[3], SCALE_LOG2, -mn1));
            m0 = mn0; m1 = mn1;
            l0 = fmaf(l0, al0, p0 + p2);
            l1 = fmaf(l1, al1, p1 + p3);
            const uint32_t pb0 = movtrans(pack_bf16(p0, p1));
            const uint32_t pb1 = movtrans(pack_bf16(p2, p3));
#pragma unroll
            for (int i = 0; i < 16; ++i) { o[i][0] *= al0; o[i][1] *= al1; o[i][2] *= al0; o[i][3] *= al1; }
            {
                const uint32_t slot = ring + s3 * (8 * SLOT);
                mbar_wait_warp(fullw + 64 * s3, ph);
                TSQ();
#pragma unroll
                for (int mt = 0; mt < 16; ++mt) {
                    uint32_t a[4];
                    ldsm4t(a, slot + (mt >> 2) * 2048 + voff[mt & 3]);
                    mma16816(o[mt], a, pb0, pb1);
                }
                __syncwarp();
                if (lane == 0) mbar_arrive(emptyw + 64 * s3);
                if (++s3 == 3) { s3 = 0; ph ^= 1; }
            }
        }
        uint8_t* red = smem + SM_RED;
        float4* ml = reinterpret_cast<float4*>(smem + SM_ML);
#pragma unroll
        for (int x = 4; x <= 16; x <<= 1) {
            l0 += __shfl_xor_sync(0xffffffffu, l0, x);
            l1 += __shfl_xor_sync(0xffffffffu, l1, x);
        }
        if (t == 0) {
            float2* dst = reinterpret_cast<float2*>(red + w * 2048);
#pragma unroll
            for (int mt = 0; mt < 16; ++mt) {
                dst[mt * 16 + g] = make_float2(o[mt][0], o[mt][1]);
                dst[mt * 16 + 8 + g] = make_float2(o[mt][2], o[mt][3]);
            }
            if (lane == 0) ml[w] = make_float4(m0, m1, l0, l1);
        }
        asm volatile("bar.sync 3, 288;" ::: "memory");
        float4 mw[8];
        float2 rv[8];
#pragma unroll
        for (int i = 0; i < 8; ++i) { mw[i] = ml[i]; rv[i] = reinterpret_cast<const float2*>(red + i * 2048)[tid]; }
        float M0 = mw[0].x, M1 = mw[0].y;
#pragma unroll
        for (int i = 1; i < 8; ++i) { M0 = fmaxf(M0, mw[i].x); M1 = fmaxf(M1, mw[i].y); }
        float O0 = 0.f, O1 = 0.f, L0 = 0.f, L1 = 0.f;
#pragma unroll
        for (int i = 0; i < 8; ++i) {
            const float a0 = ex2(mw[i].x - M0), a1 = ex2(mw[i].y - M1);
            O0 = fmaf(a0, rv[i].x, O0); O1 = fmaf(a1, rv[i].y, O1);
            L0 = fmaf(a0, mw[i].z, L0); L1 = fmaf(a1, mw[i].w, L1);
        }
        uint32_t* rec = scratch + OFF_REC + (tm * 8 + w) * REC_CTA;
        st_pub(rec + r * 32 + lane, encf(O0));
        st_pub(rec + (8 + r) * 32 + lane, encf(O1));
        st_pub_if(lane < 8, rec + 512 + r * 8 + lane, encf(lane == 0 ? M0 : L0));
        st_pub_if(lane < 8, rec + 512 + (8 + r) * 8 + lane, encf(lane == 0 ? M1 : L1));
    }

    uint32_t* const g_p = scratch + OFF_P + tm * 2048;
    uint32_t* const g_ml = scratch + OFF_ML + tm * 256;
    {
        float* const S = reinterpret_cast<float*>(smem + SM_SC) + w * 64;
        uint32_t qf[32];
#pragma unroll
        for (int ks = 0; ks < 16; ++ks) {
            const uint32_t a = qs[(g & 1) * 128 + ks * 8 + t], b = qs[(g & 1) * 128 + ks * 8 + 4 + t];
            qf[2 * ks] = a; qf[2 * ks + 1] = b;
        }
#pragma unroll 1
        for (int it = 0; it < 2; ++it) {
            const uint32_t slot = ring + s3 * (8 * SLOT);
            mbar_wait_warp(fullw + 64 * s3, ph);
            TSQ();
            float acc[4][4];
#pragma unroll
            for (int c = 0; c < 4; ++c) { acc[c][0] = 0.f; acc[c][1] = 0.f; acc[c][2] = 0.f; acc[c][3] = 0.f; }
#pragma unroll
            for (int ks = 0; ks < 16; ++ks) {
                uint32_t a[4];
                ldsm4(a, slot + (ks >> 2) * 2048 + koff[ks & 3]);
                mma16816(acc[ks & 3], a, qf[2 * ks], qf[2 * ks + 1]);
            }
            __syncwarp();
            if (lane == 0) mbar_arrive(emptyw + 64 * s3);
            if (++s3 == 3) { s3 = 0; ph ^= 1; }
            const float s0 = (acc[0][0] + acc[1][0]) + (acc[2][0] + acc[3][0]), s1 = (acc[0][1] + acc[1][1]) + (acc[2][1] + acc[3][1]);
            const float s2 = (acc[0][2] + acc[1][2]) + (acc[2][2] + acc[3][2]), s3_ = (acc[0][3] + acc[1][3]) + (acc[2][3] + acc[3][3]);
            const float sv = (t & 2) ? ((t & 1) ? s3_ : s2) : ((t & 1) ? s1 : s0);
            S[(t & 1) * 32 + it * 16 + (t >> 1) * 8 + g] = sv;
        }
        __syncwarp();
        const int hd = (lane >> 2) & 1, tt = lane & 3;
        float2 sv[4];
#pragma unroll
        for (int c = 0; c < 4; ++c) sv[c] = *reinterpret_cast<const float2*>(S + hd * 32 + c * 8 + 2 * tt);
        float mx = fmaxf(fmaxf(fmaxf(sv[0].x, sv[0].y), fmaxf(sv[1].x, sv[1].y)), fmaxf(fmaxf(sv[2].x, sv[2].y), fmaxf(sv[3].x, sv[3].y)));
        mx = fmaxf(mx, __shfl_xor_sync(0xffffffffu, mx, 1));
        mx = fmaxf(mx, __shfl_xor_sync(0xffffffffu, mx, 2));
        const float m = mx * SCALE_LOG2;
        float l = 0.f;
        uint32_t pw[4];
#pragma unroll
        for (int c = 0; c < 4; ++c) {
            const float p0 = ex2(fmaf(sv[c].x, SCALE_LOG2, -m)), p1 = ex2(fmaf(sv[c].y, SCALE_LOG2, -m));
            l += p0 + p1;
            pw[c] = enc(pack_bf16(p0, p1));
        }
        l += __shfl_xor_sync(0xffffffffu, l, 1);
        l += __shfl_xor_sync(0xffffffffu, l, 2);
        st_pub4_if(lane < 8, g_p + (r * 8 + w) * 32 + lane * 4, pw[0], pw[1], pw[2], pw[3]);
        st_pub2_if((lane & 27) == 0, g_ml + (r * 8 + w) * 4 + hd * 2, encf(m), encf(l));
    }

    uint32_t voff[2];
    {
        const int vkey = (lane & 7) + 8 * (lane >> 4), vhi = (lane >> 3) & 1;
#pragma unroll
        for (int c = 0; c < 2; ++c) voff[c] = vkey * 64 + (((2 * c + vhi) ^ ((lane >> 1) & 3)) << 4);
    }
    const int wx = w;
    uint32_t bw[2][7][4];
    auto load_wo = [&](int half, int grp, uint32_t par) {
        mbar_wait_warp(full0 + 64 * grp + 8 * (lane & 3) + 32 * half, par);
        const uint32_t wbase = sbase + (grp * 8 + (lane >> 3)) * SLOT + (lane & 7) * 128 + half * 4 * SLOT;
#pragma unroll
        for (int nt = 0; nt < 7; ++nt) {
            const int cc = 7 * wx + nt;
            ldsm4t(bw[half][nt], wbase + (cc >> 3) * 1024 + (((cc & 7) ^ (lane & 7)) << 4));
        }
    };
    float fo[4], fv[3];
    auto project = [&](int seg, uint32_t ow, int grp, uint32_t par) {
        fo[0] = fo[1] = fo[2] = fo[3] = 0.f;
        uint32_t af[4][4];
#pragma unroll
        for (int ks = 0; ks < 4; ++ks) {
            af[ks][0] = __shfl_sync(0xffffffffu, ow, ks * 8 + t);
            af[ks][2] = __shfl_sync(0xffffffffu, ow, ks * 8 + 4 + t);
            af[ks][1] = 0u; af[ks][3] = 0u;
        }
        float c[7][4], c2[7][4];
        uint32_t wo[4];
#pragma unroll
        for (int u = 0; u < 4; ++u) {
            const int cc = 7 * wx + 2 * u + (u < 3 ? lane >> 4 : 0);
            wo[u] = sbase + (grp * 8 + ((lane >> 3) & 1)) * SLOT + (lane & 7) * 128 + (cc >> 3) * 1024 + (((cc & 7) ^ (lane & 7)) << 4);
        }
#pragma unroll
        for (int nt = 0; nt < 7; ++nt) {
            c[nt][0] = c[nt][1] = c[nt][2] = c[nt][3] = 0.f;
            c2[nt][0] = c2[nt][1] = 0.f;
        }
#pragma unroll
        for (int ks = 0; ks < 4; ++ks) {
            mbar_wait_warp(full0 + 64 * grp + 16 * ks + 8 * (lane & 1), par);
            uint32_t b[3][4], b6[2];
#pragma unroll
            for (int u = 0; u < 3; ++u) ldsm4t(b[u], wo[u] + ks * 2 * SLOT);
            ldsm2t(b6, wo[3] + ks * 2 * SLOT);
#pragma unroll
            for (int u = 0; u < 3; ++u) {
                mma16816(c[2 * u], af[ks], b[u][0], b[u][1]);
                mma16816(c[2 * u + 1], af[ks], b[u][2], b[u][3]);
            }
            mma16816(c[6], af[ks], b6[0], b6[1]);
        }
        if (FIN_ATOM == 1 || seg == 1) {
            constexpr int NG = (14 + ATOM_W - 1) / ATOM_W;
            float val[15];
#pragma unroll
            for (int nt = 0; nt < 7; ++nt) {
                val[2 * nt] = PROJ_PAIR ? c[nt][0] : c[nt][0] + c2[nt][0];
                val[2 * nt + 1] = PROJ_PAIR ? c[nt][1] : c[nt][1] + c2[nt][1];
            }
            val[14] = 0.f;
            float v0 = val[0], v1 = val[1], v2 = ATOM_W == 3 ? val[2] : 0.f;
#pragma unroll
            for (int k = 1; k < NG; ++k) {
                v0 = g == k ? val[ATOM_W * k] : v0; v1 = g == k ? val[ATOM_W * k + 1] : v1;
                if (ATOM_W == 3) v2 = g == k ? val[ATOM_W * k + 2] : v2;
            }
            uint32_t* acc = g_outp + seg * (112 * 512) + ((ab * 8 + wx) * (NG * 4) + g * 4 + t) * ACC_STRIDE;
            asm volatile("{\n.reg .pred p;\nsetp.ne.u32 p, %9, 0;\n"
                         "@p atom.relaxed.gpu.global.add.v4.f32 {%0,%1,%2,%3}, [%4], {%5,%6,%7,%8};\n}"
                         : "+f"(fo[0]), "+f"(fo[1]), "+f"(fo[2]), "+f"(fo[3])
                         : "l"(acc), "f"(v0), "f"(v1), "f"(v2), "f"(1.0f), "r"((uint32_t)(g < NG)) : "memory");
            fv[0] = v0; fv[1] = v1; fv[2] = v2;
            return;
        }
        float v0 = c[0][0] + c2[0][0], v1 = c[0][1] + c2[0][1];
#pragma unroll
        for (int nt = 1; nt < 7; ++nt) {
            const float u0 = c[nt][0] + c2[nt][0], u1 = c[nt][1] + c2[nt][1];
            v0 = g == nt ? u0 : v0; v1 = g == nt ? u1 : v1;
        }
        uint32_t* dst = g_outp + ((seg * 2 + ab) * 56 + 7 * wx + g) * 512 + (ag * 8 + r) * 8 + 2 * t;
        st_pub2_if(g < 7, dst, encf(v0), encf(v1));
    };
#pragma unroll 1
    for (int seg = 0; seg < 2; ++seg) {
        uint32_t ow;
        if (seg == 0) {
            if (w < 4) {
                const int hh = tid >> 6, dq = (tid >> 3) & 7, sp = tid & 7;
                const uint32_t* myrec = scratch + OFF_REC + (tm * 8 + r) * REC_CTA;
                uint4 v;
                uint2 ml;
                int it = 0;
#pragma unroll 1
                while (true) {
                    v = ld_poll4(myrec + (hh * 8 + sp) * 32 + dq * 4);
                    ml = ld_poll2(myrec + 512 + (hh * 8 + sp) * 8);
                    if (__all_sync(0xffffffffu, v.x && v.y && v.z && v.w && ml.x && ml.y)) break;
                    if (++it > SPIN_LIMIT || ABORTED) TRAPX(6)
                }
                st_zero4_if(tid < 16, g_q + ((r >> 2) * 2 + ab) * 2048 + ag * 256 + (r & 3) * 64 + tid * 4);
                const float m = decf(ml.x), l = decf(ml.y);
                float M = m;
#pragma unroll
                for (int x = 1; x <= 4; x <<= 1) M = fmaxf(M, __shfl_xor_sync(0xffffffffu, M, x));
                const float a = ex2(m - M);
                float L = a * l, o0 = a * decf(v.x), o1 = a * decf(v.y), o2 = a * decf(v.z), o3 = a * decf(v.w);
#pragma unroll
                for (int x = 1; x <= 4; x <<= 1) {
                    L += __shfl_xor_sync(0xffffffffu, L, x);
                    o0 += __shfl_xor_sync(0xffffffffu, o0, x);
                    o1 += __shfl_xor_sync(0xffffffffu, o1, x);
                    o2 += __shfl_xor_sync(0xffffffffu, o2, x);
                    o3 += __shfl_xor_sync(0xffffffffu, o3, x);
                }
                const float inv = __frcp_rn(L);
                const uint2 pk = make_uint2(pack_bf16(o0 * inv, o1 * inv), pack_bf16(o2 * inv, o3 * inv));
                if (sp == 0) *reinterpret_cast<uint2*>(smem + SM_OS + hh * 64 + dq * 8) = pk;
            }
            bar_consumers();
            ow = reinterpret_cast<const uint32_t*>(smem + SM_OS)[lane];
        } else {
            const uint32_t* mp = g_ml + lane * 4;
            const uint32_t* pp = g_p + w * 256 + (lane & 7) * 4;
            uint4 a, b, pv[8];
            {
                int it = 0;
#pragma unroll 1
                while (true) {
                    a = ld_poll4(mp);
                    b = ld_poll4(mp + 128);
                    bool ok = true;
#pragma unroll
                    for (int i = 0; i < 8; ++i) pv[i] = ld_poll4(pp + i * 32);
#pragma unroll
                    for (int i = 0; i < 8; ++i) ok = ok && pv[i].x && pv[i].y && pv[i].z && pv[i].w;
                    if (__all_sync(0xffffffffu, ok && a.x && a.y && a.z && a.w && b.x && b.y && b.z && b.w)) break;
                    if (++it > SPIN_LIMIT || ABORTED) TRAPX(7)
                }
            }
            float f[8][2];
            {
                const float ma0 = decf(a.x), ma1 = decf(a.z), mb0 = decf(b.x), mb1 = decf(b.z);
                float M0 = fmaxf(ma0, mb0), M1 = fmaxf(ma1, mb1);
#pragma unroll
                for (int x = 1; x <= 16; x <<= 1) {
                    M0 = fmaxf(M0, __shfl_xor_sync(0xffffffffu, M0, x));
                    M1 = fmaxf(M1, __shfl_xor_sync(0xffffffffu, M1, x));
                }
                const float fa0 = ex2(ma0 - M0), fa1 = ex2(ma1 - M1), fb0 = ex2(mb0 - M0), fb1 = ex2(mb1 - M1);
                float L0 = fmaf(fa0, decf(a.y), fb0 * decf(b.y)), L1 = fmaf(fa1, decf(a.w), fb1 * decf(b.w));
#pragma unroll
                for (int x = 1; x <= 16; x <<= 1) {
                    L0 += __shfl_xor_sync(0xffffffffu, L0, x);
                    L1 += __shfl_xor_sync(0xffffffffu, L1, x);
                }
                const float u0 = (w < 4 ? fa0 : fb0) * __frcp_rn(L0), u1 = (w < 4 ? fa1 : fb1) * __frcp_rn(L1);
#pragma unroll
                for (int ks = 0; ks < 8; ++ks) {
                    f[ks][0] = __shfl_sync(0xffffffffu, u0, (w & 3) * 8 + ks);
                    f[ks][1] = __shfl_sync(0xffffffffu, u1, (w & 3) * 8 + ks);
                }
            }
            float acc[8][2][4];
#pragma unroll
            for (int it = 0; it < 2; ++it) {
                const uint32_t slot = ring + s3 * (8 * SLOT);
                mbar_wait_warp(fullw + 64 * s3, ph);
                TSQ();
#pragma unroll
                for (int ks = 0; ks < 8; ++ks) {
#pragma unroll
                    for (int mt = 0; mt < 2; ++mt) {
                        uint32_t av[4];
                        ldsm4t(av, slot + ks * 1024 + voff[mt]);
                        if (it == 0) { acc[ks][mt][0] = 0.f; acc[ks][mt][1] = 0.f; acc[ks][mt][2] = 0.f; acc[ks][mt][3] = 0.f; }
                        mma16816(acc[ks][mt], av, ~(it ? pv[ks].z : pv[ks].x), ~(it ? pv[ks].w : pv[ks].y));
                    }
                }
                if (++s3 == 3) { s3 = 0; ph ^= 1; }
            }
            float o[2][4];
#pragma unroll
            for (int mt = 0; mt < 2; ++mt) {
#pragma unroll
                for (int c = 0; c < 4; ++c) {
                    float e = 0.f, d = 0.f;
#pragma unroll
                    for (int ks = 0; ks < 8; ks += 2) { e = fmaf(f[ks][c & 1], acc[ks][mt][c], e); d = fmaf(f[ks + 1][c & 1], acc[ks + 1][mt][c], d); }
                    o[mt][c] = e + d;
                }
            }
            TS(5);
            float* const orp = reinterpret_cast<float*>(smem + SM_OR);
            const float v0 = (t & 2) ? ((t & 1) ? o[1][2] : o[1][0]) : ((t & 1) ? o[0][2] : o[0][0]);
            const float v1 = (t & 2) ? ((t & 1) ? o[1][3] : o[1][1]) : ((t & 1) ? o[0][3] : o[0][1]);
            orp[w * 64 + 8 * t + g] = v0;
            orp[w * 64 + 32 + 8 * t + g] = v1;
            bar_consumers();
            float sx = 0.f, sy = 0.f;
#pragma unroll
            for (int i = 0; i < 8; ++i) {
                const float2 v = reinterpret_cast<const float2*>(orp + i * 64)[lane];
                sx += v.x; sy += v.y;
            }
            ow = pack_bf16(sx, sy);
            TS(6);
        }
        project(seg, ow, s3, ph);
        if (seg == 0) {
            bar_consumers();
            if (lane == 0) mbar_arrive(emptyw + 64 * s3);
            if (++s3 == 3) { s3 = 0; ph ^= 1; }
        }
        if (seg == 1) { TS(9); TSX(8); }
        if (fo[3] == 63.0f) {
            __nv_bfloat16* dst = outp + ab * 896 + seg * 448 + 56 * wx + 2 * t;
#pragma unroll
            for (int k = 0; k < ATOM_W; ++k) {
                const int i = ATOM_W * g + k;
                if (i < 14) dst[8 * (i >> 1) + (i & 1)] = __float2bfloat16_rn(fo[k] + fv[k]);
            }
        }
    }

    if (FIN_ATOM != 1 && w < (FIN_ATOM ? 1 : 2) && j < 112) {
        const int fb = j >= 56, cb = j - fb * 56;
        const uint32_t* src = g_outp + (w * 112 + j) * 512 + lane * 4;
        const int col = 4 * (lane & 1) + 2 * (lane >> 4) + ((lane >> 3) & 1);
        __nv_bfloat16* dst = outp + fb * 896 + w * 448 + cb * 8 + col;
        asm volatile("" : "+l"(dst));
        uint4 v[4];
        int it = 0;
#pragma unroll 1
        while (true) {
            bool all = true;
#pragma unroll
            for (int i = 0; i < 4; ++i) v[i] = ld_poll4(src + i * 128);
#pragma unroll
            for (int i = 0; i < 4; ++i) all = all && v[i].x && v[i].y && v[i].z && v[i].w;
            if (__all_sync(0xffffffffu, all)) break;
            if (++it > SPIN_LIMIT || ABORTED) TRAPX(8)
            POLL_SLEEP(NS_FIN);
        }
        float a0 = 0.f, a1 = 0.f, a2 = 0.f, a3 = 0.f;
#pragma unroll
        for (int i = 0; i < 4; ++i) { a0 += decf(v[i].x); a1 += decf(v[i].y); a2 += decf(v[i].z); a3 += decf(v[i].w); }
        const bool u16 = lane & 16, u8 = lane & 8;
        float h0 = (u16 ? a2 : a0) + __shfl_xor_sync(0xffffffffu, u16 ? a0 : a2, 16);
        float h1 = (u16 ? a3 : a1) + __shfl_xor_sync(0xffffffffu, u16 ? a1 : a3, 16);
        float z = (u8 ? h1 : h0) + __shfl_xor_sync(0xffffffffu, u8 ? h0 : h1, 8);
        z += __shfl_xor_sync(0xffffffffu, z, 4);
        z += __shfl_xor_sync(0xffffffffu, z, 2);
        if ((lane & 6) == 0) *dst = __float2bfloat16_rn(z);
    }
    TS(10);
}

typedef CUresult (*EncodeTiledFn)(CUtensorMap*, CUtensorMapDataType, cuuint32_t, void*, const cuuint64_t*,
                                  const cuuint64_t*, const cuuint32_t*, const cuuint32_t*, CUtensorMapInterleave,
                                  CUtensorMapSwizzle, CUtensorMapL2promotion, CUtensorMapFloatOOBfill);

}

extern "C" void kernel_launch(void* const* d_in, const int* in_sizes, int n_in, void* d_out, int out_size) {
    (void)in_sizes; (void)n_in; (void)out_size;
    static EncodeTiledFn encode = nullptr;
    static uint32_t* scratch = nullptr;
    if (!encode) {
        void* fn = nullptr;
        cudaDriverEntryPointQueryResult qr;
        cudaGetDriverEntryPoint("cuTensorMapEncodeTiled", &fn, cudaEnableDefault, &qr);
        encode = (EncodeTiledFn)fn;
        void* sp = nullptr;
        cudaGetSymbolAddress(&sp, g_scratch);
        scratch = (uint32_t*)sp;
        cudaFuncSetAttribute(fused_decode_kernel, cudaFuncAttributeMaxDynamicSharedMemorySize, SM_TOTAL);
    }
    Maps P;
    for (int p = 0; p < 2; ++p) {
        const cuuint32_t es[3] = {1, 1, 1};
        {
            const cuuint64_t dims[3] = {64, 448, 64};
            const cuuint64_t strides[2] = {8192, 128};
            const cuuint32_t box[3] = {64, 56, 1};
            encode(&P.m[p], CU_TENSOR_MAP_DATA_TYPE_BFLOAT16, 3, d_in[5 * p + 3], dims, strides, box, es,
                   CU_TENSOR_MAP_INTERLEAVE_NONE, CU_TENSOR_MAP_SWIZZLE_NONE, CU_TENSOR_MAP_L2_PROMOTION_NONE,
                   CU_TENSOR_MAP_FLOAT_OOB_FILL_NONE);
        }
        {
            const cuuint64_t dims[3] = {64, 131072, 4};
            const cuuint64_t strides[2] = {512, 128};
            const cuuint32_t box[3] = {64, 16, 4};
            encode(&P.m[2 + 2 * p], CU_TENSOR_MAP_DATA_TYPE_BFLOAT16, 3, d_in[5 * p + 1], dims, strides, box, es,
                   CU_TENSOR_MAP_INTERLEAVE_NONE, CU_TENSOR_MAP_SWIZZLE_128B, CU_TENSOR_MAP_L2_PROMOTION_NONE,
                   CU_TENSOR_MAP_FLOAT_OOB_FILL_NONE);
        }
        if (p == 0) {
            const cuuint64_t dims[3] = {64, 131072, 4};
            const cuuint64_t strides[2] = {512, 128};
            const cuuint32_t box[3] = {64, 16, 4};
            encode(&P.m[3], CU_TENSOR_MAP_DATA_TYPE_BFLOAT16, 3, d_in[2], dims, strides, box, es,
                   CU_TENSOR_MAP_INTERLEAVE_NONE, CU_TENSOR_MAP_SWIZZLE_128B, CU_TENSOR_MAP_L2_PROMOTION_NONE,
                   CU_TENSOR_MAP_FLOAT_OOB_FILL_NONE);
        } else {
            const cuuint64_t dims[3] = {256, 131072, 1};
            const cuuint64_t strides[2] = {512, 512ull * 131072};
            const cuuint32_t box[3] = {32, 128, 1};
            encode(&P.m[5], CU_TENSOR_MAP_DATA_TYPE_BFLOAT16, 3, d_in[7], dims, strides, box, es,
                   CU_TENSOR_MAP_INTERLEAVE_NONE, CU_TENSOR_MAP_SWIZZLE_64B, V_PROMO,
                   CU_TENSOR_MAP_FLOAT_OOB_FILL_NONE);
        }
        const cuuint64_t dims[3] = {64, 4096, 7};
        const cuuint64_t strides[2] = {896, 128};
        const cuuint32_t box[3] = {64, 8, 7};
        encode(&P.m[6 + p], CU_TENSOR_MAP_DATA_TYPE_BFLOAT16, 3, d_in[5 * p + 4], dims, strides, box, es,
               CU_TENSOR_MAP_INTERLEAVE_NONE, CU_TENSOR_MAP_SWIZZLE_128B, CU_TENSOR_MAP_L2_PROMOTION_NONE,
               CU_TENSOR_MAP_FLOAT_OOB_FILL_NONE);
    }
    fused_decode_kernel<<<NCTA, NTHR, SM_TOTAL, cudaStreamPerThread>>>(d_in[0], d_in[5], scratch, (__nv_bfloat16*)d_out, P);
}
```

```cpp
#include <cuda_runtime.h>
#include <cuda.h>
#include <cuda_bf16.h>
#include <stdint.h>

namespace {

constexpr int NCTA = 128;
constexpr int NTHR = 320;
constexpr int SLOT = 8192;
constexpr int SM_RED = 24 * SLOT;
constexpr int SM_SC = SM_RED + 16384;
constexpr int SM_OR = SM_SC + 2048;
constexpr int SM_QS = SM_OR + 2048;
constexpr int SM_ML = SM_QS + 2048;
constexpr int SM_OS = SM_ML + 128;
constexpr int SM_BAR = SM_OS + 128;
constexpr int SM_FLAG = SM_BAR + 384;
constexpr int SM_TOTAL = SM_FLAG + 32 + 1024;
constexpr int SPIN_LIMIT = 1 << 20;
constexpr int NQ = 22;
constexpr int Q_WOA = 18, Q_WOB = 21;

constexpr int W_MAIN = 9;
constexpr int W_WO = 7;
constexpr int W_LO = 3;
constexpr int W_HI = 12, W_HI_WO = 14;
constexpr int WO_WT = 7;
constexpr int NS_PACE = 200;
constexpr float RHO0 = 3.65f;
constexpr float RHO_A = 0.25f;
constexpr float PACE_AGE = 0.5f;
constexpr int NS_Q = 40;

constexpr int Q_WORDS = 2 * 2 * 2048;
constexpr int P_WORDS = 16 * 2048;
constexpr int ML_WORDS = 16 * 64 * 4;
constexpr int REC_CTA = 640;
constexpr int REC_WORDS = NCTA * REC_CTA;
constexpr int NACC = 320;
constexpr int ACC_STRIDE = 32;
constexpr int OUTP_WORDS = 2 * NACC * ACC_STRIDE;
constexpr int OFF_P = Q_WORDS, OFF_ML = OFF_P + P_WORDS, OFF_REC = OFF_ML + ML_WORDS, OFF_OUTP = OFF_REC + REC_WORDS;
constexpr int OFF_PACE = OFF_OUTP + OUTP_WORDS;
constexpr int PACE_WORDS = 64;

struct alignas(64) Maps {
    CUtensorMap m[8];
};

constexpr int SCRATCH_WORDS = OFF_PACE + PACE_WORDS;
__device__ __align__(128) uint32_t g_scratch[SCRATCH_WORDS];

__device__ __forceinline__ uint32_t enc(uint32_t bits) { return max(~bits, 1u); }
__device__ __forceinline__ uint32_t encf(float f) { return enc(__float_as_uint(f)); }
__device__ __forceinline__ float decf(uint32_t w) { return __uint_as_float(~w); }

__device__ __forceinline__ uint32_t ld_poll(const uint32_t* p) {
    uint32_t v;
    asm volatile("ld.relaxed.gpu.global.u32 %0, [%1];" : "=r"(v) : "l"(p) : "memory");
    return v;
}
__device__ __forceinline__ uint2 ld_poll2(const uint32_t* p) {
    uint2 v;
    asm volatile("ld.relaxed.gpu.global.v2.u32 {%0,%1}, [%2];" : "=r"(v.x), "=r"(v.y) : "l"(p) : "memory");
    return v;
}
__device__ __forceinline__ uint4 ld_poll4(const uint32_t* p) {
    uint4 v;
    asm volatile("ld.relaxed.gpu.global.v4.u32 {%0,%1,%2,%3}, [%4];"
                 : "=r"(v.x), "=r"(v.y), "=r"(v.z), "=r"(v.w) : "l"(p) : "memory");
    return v;
}
__device__ __forceinline__ void st_zero4_if(bool pred, uint32_t* p) {
    asm volatile("{\n.reg .pred p;\nsetp.ne.u32 p, %2, 0;\n@p st.relaxed.gpu.global.v4.u32 [%0], {%1,%1,%1,%1};\n}"
                 ::"l"(p), "r"(0u), "r"((uint32_t)pred) : "memory");
}
__device__ __forceinline__ void st_pub(uint32_t* p, uint32_t v) {
    asm volatile("st.relaxed.gpu.global.u32 [%0], %1;" ::"l"(p), "r"(v) : "memory");
}
__device__ __forceinline__ void st_pub_if(bool pred, uint32_t* p, uint32_t v) {
    asm volatile("{\n.reg .pred p;\nsetp.ne.u32 p, %2, 0;\n@p st.relaxed.gpu.global.u32 [%0], %1;\n}"
                 ::"l"(p), "r"(v), "r"((uint32_t)pred) : "memory");
}
__device__ __forceinline__ void st_pub2_if(bool pred, uint32_t* p, uint32_t a, uint32_t b) {
    asm volatile("{\n.reg .pred p;\nsetp.ne.u32 p, %3, 0;\n@p st.relaxed.gpu.global.v2.u32 [%0], {%1,%2};\n}"
                 ::"l"(p), "r"(a), "r"(b), "r"((uint32_t)pred) : "memory");
}
__device__ __forceinline__ void st_pub4_if(bool pred, uint32_t* p, uint32_t a, uint32_t b, uint32_t c, uint32_t d) {
    asm volatile("{\n.reg .pred p;\nsetp.ne.u32 p, %5, 0;\n@p st.relaxed.gpu.global.v4.u32 [%0], {%1,%2,%3,%4};\n}"
                 ::"l"(p), "r"(a), "r"(b), "r"(c), "r"(d), "r"((uint32_t)pred) : "memory");
}
__device__ __forceinline__ void st_zero4(uint32_t* p) {
    asm volatile("st.relaxed.gpu.global.v4.u32 [%0], {%1,%1,%1,%1};" ::"l"(p), "r"(0u) : "memory");
}
__device__ __forceinline__ uint32_t ldg_u32(const void* p) {
    uint32_t v;
    asm volatile("ld.global.u32 %0, [%1];" : "=r"(v) : "l"(p) : "memory");
    return v;
}

__device__ __forceinline__ void mbar_init(uint32_t bar, uint32_t cnt) {
    asm volatile("mbarrier.init.shared::cta.b64 [%0], %1;" ::"r"(bar), "r"(cnt) : "memory");
}
__device__ __forceinline__ void mbar_expect_tx(uint32_t bar, uint32_t bytes) {
    asm volatile("mbarrier.arrive.expect_tx.shared::cta.b64 _, [%0], %1;" ::"r"(bar), "r"(bytes) : "memory");
}
__device__ __forceinline__ void mbar_arrive(uint32_t bar) {
    asm volatile("mbarrier.arrive.shared::cta.b64 _, [%0];" ::"r"(bar) : "memory");
}
__device__ __forceinline__ bool mbar_try(uint32_t bar, uint32_t parity) {
    uint32_t ok;
    asm volatile("{\n.reg .pred p;\nmbarrier.try_wait.parity.shared::cta.b64 p, [%1], %2;\nselp.u32 %0, 1, 0, p;\n}"
                 : "=r"(ok) : "r"(bar), "r"(parity) : "memory");
    return ok;
}
__device__ __forceinline__ bool mbar_test(uint32_t bar, uint32_t parity) {
    uint32_t ok;
    asm volatile("{\n.reg .pred p;\nmbarrier.test_wait.parity.shared::cta.b64 p, [%1], %2;\nselp.u32 %0, 1, 0, p;\n}"
                 : "=r"(ok) : "r"(bar), "r"(parity) : "memory");
    return ok;
}
__device__ __forceinline__ void mbar_wait_warp(uint32_t bar, uint32_t parity) {
    int it = 0;
#pragma unroll 1
    while (!__all_sync(0xffffffffu, mbar_try(bar, parity))) { if (++it > SPIN_LIMIT) __trap(); }
}
__device__ __forceinline__ void tma3d(uint32_t dst, const CUtensorMap* m, int col, int row, int chunk, uint32_t bar, uint64_t pol) {
    asm volatile("cp.async.bulk.tensor.3d.shared::cluster.global.mbarrier::complete_tx::bytes.L2::cache_hint"
                 " [%0], [%1, {%3, %4, %5}], [%2], %6;"
                 ::"r"(dst), "l"(m), "r"(bar), "r"(col), "r"(row), "r"(chunk), "l"(pol) : "memory");
}
__device__ __forceinline__ void tma3d_elect(uint32_t dst, const CUtensorMap* m, int col, int row, uint32_t bar, uint32_t bytes, uint64_t pol) {
    asm volatile("{\n.reg .pred p;\nelect.sync _|p, 0xffffffff;\n"
                 "@p mbarrier.arrive.expect_tx.shared::cta.b64 _, [%2], %6;\n"
                 "@p cp.async.bulk.tensor.3d.shared::cluster.global.mbarrier::complete_tx::bytes.L2::cache_hint"
                 " [%0], [%1, {%3, %4, %5}], [%2], %7;\n}"
                 ::"r"(dst), "l"(m), "r"(bar), "r"(col), "r"(row), "r"(0), "r"(bytes), "l"(pol) : "memory");
}
__device__ __forceinline__ uint64_t stream_policy() {
    uint64_t pol;
    asm("createpolicy.fractional.L2::evict_first.b64 %0, 1.0;" : "=l"(pol));
    return pol;
}
__device__ __forceinline__ void bar_consumers() { asm volatile("bar.sync 1, 256;" ::: "memory"); }

__device__ __forceinline__ void ldsm4(uint32_t (&a)[4], uint32_t addr) {
    asm volatile("ldmatrix.sync.aligned.m8n8.x4.shared.b16 {%0,%1,%2,%3}, [%4];"
                 : "=r"(a[0]), "=r"(a[1]), "=r"(a[2]), "=r"(a[3]) : "r"(addr) : "memory");
}
__device__ __forceinline__ void ldsm4t(uint32_t (&a)[4], uint32_t addr) {
    asm volatile("ldmatrix.sync.aligned.m8n8.x4.trans.shared.b16 {%0,%1,%2,%3}, [%4];"
                 : "=r"(a[0]), "=r"(a[1]), "=r"(a[2]), "=r"(a[3]) : "r"(addr) : "memory");
}
__device__ __forceinline__ void ldsm2t(uint32_t (&a)[2], uint32_t addr) {
    asm volatile("ldmatrix.sync.aligned.m8n8.x2.trans.shared.b16 {%0,%1}, [%2];"
                 : "=r"(a[0]), "=r"(a[1]) : "r"(addr) : "memory");
}
__device__ __forceinline__ void mma16816(float (&c)[4], const uint32_t (&a)[4], uint32_t b0, uint32_t b1) {
    asm("mma.sync.aligned.m16n8k16.row.col.f32.bf16.bf16.f32 {%0,%1,%2,%3}, {%4,%5,%6,%7}, {%8,%9}, {%0,%1,%2,%3};"
        : "+f"(c[0]), "+f"(c[1]), "+f"(c[2]), "+f"(c[3])
        : "r"(a[0]), "r"(a[1]), "r"(a[2]), "r"(a[3]), "r"(b0), "r"(b1));
}
__device__ __forceinline__ uint32_t movtrans(uint32_t a) {
    uint32_t d;
    asm volatile("movmatrix.sync.aligned.m8n8.trans.b16 %0, %1;" : "=r"(d) : "r"(a));
    return d;
}
__device__ __forceinline__ float ex2(float x) {
    float y;
    asm("ex2.approx.ftz.f32 %0, %1;" : "=f"(y) : "f"(x));
    return y;
}
__device__ __forceinline__ uint32_t pack_bf16(float lo, float hi) {
    uint32_t d;
    asm("cvt.rn.bf16x2.f32 %0, %1, %2;" : "=r"(d) : "f"(hi), "f"(lo));
    return d;
}
__device__ __forceinline__ float bf_lo(uint32_t w) { return __uint_as_float(w << 16); }
__device__ __forceinline__ float bf_hi(uint32_t w) { return __uint_as_float(w & 0xffff0000u); }

constexpr float SCALE_LOG2 = 1.4426950408889634f / 16.0f;

__global__ void __launch_bounds__(NTHR, 1)
fused_decode_kernel(const void* __restrict__ xA, const void* __restrict__ xB, uint32_t* scratch, __nv_bfloat16* outp,
                    const uint8_t* __restrict__ kA, const __grid_constant__ Maps P) {
    extern __shared__ uint8_t smem_raw[];
    const int tid = threadIdx.x, w = tid >> 5, lane = tid & 31;
    const int j = blockIdx.x;
    const int op = j >> 6, jj = j & 63;
    const int r = (j & 1) | ((j >> 1) & 6), ab = (j >> 1) & 1, ag = j >> 4;
    const int tm = ab * 8 + ag;
    const uint32_t sraw = (uint32_t)__cvta_generic_to_shared(smem_raw);
    uint32_t sbase = (sraw + 1023u) & ~1023u;
    uint8_t* smem = smem_raw + (sbase - sraw);
    asm volatile("" : "+r"(sbase));
    const uint32_t full0 = sbase + SM_BAR, empty0 = full0 + 24 * 8;

    const uint64_t pol = stream_policy();
    if ((w >> 1) == 1) {
        const uint8_t* a = kA + ((size_t)tm * 8192 + ((3 * ag) & 7) * 1024 + r * 128 + 16) * 512 + (tid & 63) * 128;
        asm volatile("prefetch.global.L2 [%0];" ::"l"(a) : "memory");
    }
    if (tid == 256) {
        asm volatile("prefetch.tensormap [%0];" ::"l"(&P.m[op]) : "memory");
#pragma unroll
        for (int s = 0; s < 8; ++s) mbar_init(full0 + 8 * s, 1);
        asm volatile("fence.mbarrier_init.release.cluster;" ::: "memory");
#pragma unroll 1
        for (int cw = 0; cw < 8; ++cw) {
            mbar_expect_tx(full0 + 8 * cw, 7168);
            tma3d(sbase + cw * SLOT, &P.m[op], 0, cw * 56, jj, full0 + 8 * cw, pol);
        }
    }
    if (tid == 0) {
#pragma unroll
        for (int s = 8; s < 48; ++s) mbar_init(full0 + 8 * s, 1);
        asm volatile("fence.mbarrier_init.release.cluster;" ::: "memory");
    }
    if (w == 8) {
        if (lane >= 2 && lane < 8) asm volatile("prefetch.tensormap [%0];" ::"l"(&P.m[lane]) : "memory");
        __syncwarp();
        asm volatile("bar.sync 2, 320;" ::: "memory");
        const int rowA = tm * 8192, rowB = rowA + 6144;
        int sl = 8;
        uint32_t ph = 0;
        int kw = 8 * 16;
        uint32_t myop = (1u << 10) | 16u;
        int spin = 0;
        int q = 0, cw = 0;
        const CUtensorMap* map;
        int row, rstep, col, Wb, whi, wt, lead;
        uint32_t bytes;
        bool iswo;
        auto setup = [&]() {
            rstep = 16; col = 0; Wb = W_MAIN; bytes = SLOT; iswo = false; wt = 16; whi = W_HI;
            if (q < 16) { map = &P.m[2 + (q & 1)]; row = rowA + (((q >> 1) + 3 * ag) & 7) * 1024 + r * 128; }
            else if (q < 18) { map = &P.m[4]; row = rowB + r * 256 + (q - 16) * 128; }
            else if (q == Q_WOB || q == Q_WOA) {
                map = &P.m[q == Q_WOB ? 7 : 6]; row = ag * 512 + r * 32; rstep = 8; bytes = 7168;
                Wb = q == Q_WOB ? W_WO : W_MAIN; iswo = true; wt = WO_WT; whi = W_HI_WO;
            } else { map = &P.m[5]; row = rowB + (q - Q_WOA - 1) * 128; rstep = 256; col = r * 32; }
            lead = 16 * Wb;
        };
        setup();
#pragma unroll 1
        while (true) {
            int s2 = sl + lane - 24;
            uint32_t par = ph ^ 1;
            if (s2 >= 24) { s2 -= 24; par = ph; }
            const bool isf = lane < 24;
            const bool ok = mbar_test(isf ? full0 + 8 * lane : empty0 + 8 * s2, isf ? (lane < sl ? ph : ph ^ 1) : par);
            uint32_t c0, c1, c2, c3, now;
            asm volatile("ld.volatile.shared.v4.u32 {%0,%1,%2,%3}, [%4];"
                         : "=r"(c0), "=r"(c1), "=r"(c2), "=r"(c3) : "r"(sbase + SM_FLAG + 16) : "memory");
            asm volatile("mov.u32 %0, %%clock;" : "=r"(now));
            const int e0 = (int)(fmaf((float)min((int)(now - c1), 3500), __uint_as_float(c2), __uint_as_float(c0)) * (1.0f / NCTA));
            const uint32_t e1 = (lane == 24 && c3) ? (uint32_t)(min(max(e0, 0), 65000) + 1) << 16 : 0u;
            uint32_t fmask = __ballot_sync(0xffffffffu, ok) >> 24;
            const uint32_t fl = __reduce_add_sync(0xffffffffu, (isf && !ok) ? myop : e1);
            int infl = (fl >> 10) & 63;
            const int est = (int)(fl >> 16) - 1;
            if (lane == 0) asm volatile("st.volatile.shared.s32 [%0], %1;" ::"r"(sbase + SM_FLAG + 8), "r"(kw - (int)(fl & 1023u)) : "memory");
            if (++spin > SPIN_LIMIT) __trap();
#pragma unroll 1
            while (fmask & 1) {
                const bool go = (iswo && cw != 0) || infl < W_LO ||
                                (infl < whi && (fl >> 16 ? kw - lead <= est : infl < Wb));
                if (!go) break;
                tma3d_elect(sbase + sl * SLOT, map, col, row, full0 + 8 * sl, bytes, pol);
                if (lane == sl) myop = (1u << 10) | wt;
                spin = 0;
                ++infl;
                kw += wt;
                fmask >>= 1;
                row += rstep;
                if (rstep == 8 && cw == 3) row += 224;
                if (++sl == 24) { sl = 0; ph ^= 1; }
                if (++cw == 8) {
                    cw = 0;
                    if (++q == NQ) break;
                    setup();
                }
            }
            if (q == NQ) break;
        }
        if (lane == 0) asm volatile("st.volatile.shared.s32 [%0], %1;" ::"r"(sbase + SM_FLAG + 4), "r"(1) : "memory");
        return;
    }

    if (w == 9) {
        uint32_t* const pB = scratch + OFF_P + tm * 2048 + r * 256;
        uint32_t* const ml = scratch + OFF_ML + tm * 256 + r * 32;
        uint32_t* const rec_in = scratch + OFF_REC + (tm * 8 + r) * REC_CTA;
        uint32_t* const cleared = scratch + OFF_PACE + 32;
        if (lane < 2) asm volatile("st.shared.v4.u32 [%0], {%1, %1, %1, %1};" ::"r"(sbase + SM_FLAG + 16 * lane), "r"(0) : "memory");
        __syncwarp();
        asm volatile("bar.arrive 2, 320;" ::: "memory");
#pragma unroll
        for (int i = 0; i < 2; ++i) st_zero4(pB + i * 128 + lane * 4);
        st_zero4_if(lane < 8, ml + (lane & 7) * 4);
#pragma unroll
        for (int i = 0; i < 5; ++i) st_zero4(rec_in + i * 128 + lane * 4);
        st_zero4_if(lane < 10, scratch + OFF_OUTP + (j * 5 + min(lane >> 1, 4)) * ACC_STRIDE + (lane & 1) * 4);
        uint32_t* const prog = scratch + OFF_PACE;
        if (j == 0 && lane == 0) st_pub(prog, 0);
        __syncwarp();
        if (lane == 0) {
            uint32_t c;
            asm volatile("atom.release.gpu.global.add.u32 %0, [%1], 1;" : "=r"(c) : "l"(cleared) : "memory");
            const uint32_t target = (c & ~(uint32_t)(NCTA - 1)) + NCTA;
            int it = 0;
#pragma unroll 1
            while (true) {
                asm volatile("ld.acquire.gpu.global.u32 %0, [%1];" : "=r"(c) : "l"(cleared) : "memory");
                if ((int32_t)(c - target) >= 0) break;
                if (++it > SPIN_LIMIT) __trap();
                __nanosleep(200);
            }
        }
        __syncwarp();
        asm volatile("bar.arrive 3, 288;" ::: "memory");
        if (lane == 0) {
            int last = 0, psum = 0;
            uint32_t pts = 0;
            float rho = RHO0;
#pragma unroll 1
            for (int it = 0; it < 4096; ++it) {
                int own, done, sum;
                uint32_t t0, t1;
                asm volatile("ld.volatile.shared.s32 %0, [%1];" : "=r"(done) : "r"(sbase + SM_FLAG + 4) : "memory");
                if (done) break;
                asm volatile("ld.volatile.shared.s32 %0, [%1];" : "=r"(own) : "r"(sbase + SM_FLAG + 8) : "memory");
                asm volatile("mov.u32 %0, %%clock;" : "=r"(t0));
                asm volatile("atom.relaxed.gpu.global.add.s32 %0, [%1], %2;" : "=r"(sum) : "l"(prog), "r"(own - last) : "memory");
                asm volatile("{\n.reg .u32 t;\nadd.u32 t, %1, 0;\nmov.u32 %0, %%clock;\n}" : "=r"(t1) : "r"(sum) : "memory");
                sum += own - last;
                last = own;
                const uint32_t ts = t0 + ((t1 - t0) >> 1);
                const float per = (float)(int)(ts - pts);
                if (it >= 3) rho += ((float)(sum - psum) / per - rho) * RHO_A;
                float cur = fmaf(rho * PACE_AGE, per + (float)(int)(t1 - t0), (float)sum);
                psum = sum; pts = ts;
                if (it >= 2)
                    asm volatile("st.volatile.shared.v4.u32 [%0], {%1,%2,%3,%4};"
                                 ::"r"(sbase + SM_FLAG + 16), "r"(__float_as_uint(cur)), "r"(ts), "r"(__float_as_uint(rho)), "r"(1) : "memory");
                __nanosleep(NS_PACE);
            }
        }
        return;
    }

    uint32_t* const g_q = scratch;
    uint32_t* const g_outp = scratch + OFF_OUTP;
    const int g = lane >> 2, t = lane & 3;
    const int rg = w * 4 + (lane >> 3);
    uint32_t xa[7], xb[7];
    {
        const uint32_t* xp = (const uint32_t*)(op ? xB : xA) + rg * 7;
#pragma unroll
        for (int i = 0; i < 7; ++i) { xa[i] = ldg_u32(xp + i); xb[i] = ldg_u32(xp + 224 + i); }
    }
    asm volatile("bar.sync 2, 320;" ::: "memory");
    uint4 wv[14];
    mbar_wait_warp(full0 + 8 * w, 0);
    {
        const uint4* wq = reinterpret_cast<const uint4*>(smem + w * SLOT) + (lane >> 3) * (14 * 8) + (lane & 7);
#pragma unroll
        for (int i = 0; i < 14; ++i) wv[i] = wq[i * 8];
    }

    {
        float acc[2][8];
#pragma unroll
        for (int c = 0; c < 8; ++c) { acc[0][c] = 0.f; acc[1][c] = 0.f; }
#pragma unroll
        for (int i = 0; i < 14; ++i) {
            const float x0 = (i & 1) ? bf_hi(xa[i >> 1]) : bf_lo(xa[i >> 1]);
            const float x1 = (i & 1) ? bf_hi(xb[i >> 1]) : bf_lo(xb[i >> 1]);
            const uint32_t ww[4] = {wv[i].x, wv[i].y, wv[i].z, wv[i].w};
#pragma unroll
            for (int c = 0; c < 4; ++c) {
                const float a = bf_lo(ww[c]), b = bf_hi(ww[c]);
                acc[0][2 * c] = fmaf(x0, a, acc[0][2 * c]); acc[0][2 * c + 1] = fmaf(x0, b, acc[0][2 * c + 1]);
                acc[1][2 * c] = fmaf(x1, a, acc[1][2 * c]); acc[1][2 * c + 1] = fmaf(x1, b, acc[1][2 * c + 1]);
            }
        }
        __syncwarp();
        if (lane == 0) mbar_arrive(empty0 + 8 * w);
        const bool u16 = lane & 16, u8 = lane & 8;
        float h[8];
#pragma unroll
        for (int c = 0; c < 8; ++c) {
            const float send = u16 ? acc[0][c] : acc[1][c], keep = u16 ? acc[1][c] : acc[0][c];
            h[c] = keep + __shfl_xor_sync(0xffffffffu, send, 16);
        }
        float q4[4];
#pragma unroll
        for (int c = 0; c < 4; ++c) {
            const float send = u8 ? h[c] : h[4 + c], keep = u8 ? h[4 + c] : h[c];
            q4[c] = keep + __shfl_xor_sync(0xffffffffu, send, 8);
        }
        float* qred = reinterpret_cast<float*>(smem + SM_RED);
        *reinterpret_cast<float4*>(qred + w * 128 + (lane >> 4) * 64 + (lane & 7) * 8 + ((lane >> 3) & 1) * 4) =
            make_float4(q4[0], q4[1], q4[2], q4[3]);
        bar_consumers();
        if (tid < 64) {
            float s0 = 0.f, s1 = 0.f;
#pragma unroll
            for (int i = 0; i < 8; ++i) {
                const float2 v = reinterpret_cast<const float2*>(qred + i * 128)[tid];
                s0 += v.x; s1 += v.y;
            }
            st_pub(g_q + (op * 2 + (tid >> 5)) * 2048 + jj * 32 + (tid & 31), enc(pack_bf16(s0, s1)));
        }
    }

    uint32_t* qs = reinterpret_cast<uint32_t*>(smem + SM_QS);
    {
        const uint32_t* qB = g_q + (2 + ab) * 2048 + ag * 256 + tid;
        const uint32_t* qA = g_q + ab * 2048 + ag * 256 + tid;
        uint32_t a = 0, b = 0;
        int it = 0;
#pragma unroll 1
        while (true) {
            if (!b) b = ld_poll(qB);
            if (!a) a = ld_poll(qA);
            if (__all_sync(0xffffffffu, a && b)) break;
            if (++it > SPIN_LIMIT) __trap();
            __nanosleep(NS_Q);
        }
        qs[tid] = ~b;
        qs[256 + tid] = ~a;
        bar_consumers();
    }

    const uint32_t ring = sbase + w * SLOT;
    const uint32_t fullw = full0 + 8 * w, emptyw = empty0 + 8 * w;
    int s3 = 1;
    uint32_t ph = 0;
    uint32_t koff[4];
    {
        const int kkey = (lane & 7) + 8 * ((lane >> 3) & 1), khi = lane >> 4;
#pragma unroll
        for (int c = 0; c < 4; ++c) koff[c] = kkey * 128 + (((2 * c + khi) ^ (lane & 7)) << 4);
    }
    {
        uint32_t voff[4];
        const int vkey = (lane & 7) + 8 * (lane >> 4), vhi = (lane >> 3) & 1;
#pragma unroll
        for (int c = 0; c < 4; ++c) voff[c] = vkey * 128 + (((2 * c + vhi) ^ (lane & 7)) << 4);
        float o[16][4];
        uint32_t qf[32];
#pragma unroll
        for (int i = 0; i < 16; ++i) { o[i][0] = 0.f; o[i][1] = 0.f; o[i][2] = 0.f; o[i][3] = 0.f; }
        float m0 = -INFINITY, m1 = -INFINITY, l0 = 0.f, l1 = 0.f;
#pragma unroll
        for (int ks = 0; ks < 16; ++ks) {
            const uint32_t a = qs[256 + (g & 1) * 128 + ks * 8 + t], b = qs[256 + (g & 1) * 128 + ks * 8 + 4 + t];
            qf[2 * ks] = g < 2 ? a : 0u; qf[2 * ks + 1] = g < 2 ? b : 0u;
        }
#pragma unroll 1
        for (int it = 0; it < 8; ++it) {
            float sc[4];
            {
                const uint32_t slot = ring + s3 * (8 * SLOT);
                mbar_wait_warp(fullw + 64 * s3, ph);
                float acc[4][4];
#pragma unroll
                for (int c = 0; c < 4; ++c) { acc[c][0] = 0.f; acc[c][1] = 0.f; acc[c][2] = 0.f; acc[c][3] = 0.f; }
#pragma unroll
                for (int ks = 0; ks < 16; ++ks) {
                    uint32_t a[4];
                    ldsm4(a, slot + (ks >> 2) * 2048 + koff[ks & 3]);
                    mma16816(acc[ks & 3], a, qf[2 * ks], qf[2 * ks + 1]);
                }
                __syncwarp();
                if (lane == 0) mbar_arrive(emptyw + 64 * s3);
                if (++s3 == 3) { s3 = 0; ph ^= 1; }
#pragma unroll
                for (int i = 0; i < 4; ++i) sc[i] = (acc[0][i] + acc[1][i]) + (acc[2][i] + acc[3][i]);
            }
            float mx0 = fmaxf(sc[0], sc[2]), mx1 = fmaxf(sc[1], sc[3]);
#pragma unroll
            for (int x = 4; x <= 16; x <<= 1) {
                mx0 = fmaxf(mx0, __shfl_xor_sync(0xffffffffu, mx0, x));
                mx1 = fmaxf(mx1, __shfl_xor_sync(0xffffffffu, mx1, x));
            }
            const float mn0 = fmaxf(m0, mx0 * SCALE_LOG2), mn1 = fmaxf(m1, mx1 * SCALE_LOG2);
            const float al0 = ex2(m0 - mn0), al1 = ex2(m1 - mn1);
            const float p0 = ex2(fmaf(sc[0], SCALE_LOG2, -mn0)), p1 = ex2(fmaf(sc[1], SCALE_LOG2, -mn1));
            const float p2 = ex2(fmaf(sc[2], SCALE_LOG2, -mn0)), p3 = ex2(fmaf(sc[3], SCALE_LOG2, -mn1));
            m0 = mn0; m1 = mn1;
            l0 = fmaf(l0, al0, p0 + p2);
            l1 = fmaf(l1, al1, p1 + p3);
            const uint32_t pb0 = movtrans(pack_bf16(p0, p1));
            const uint32_t pb1 = movtrans(pack_bf16(p2, p3));
#pragma unroll
            for (int i = 0; i < 16; ++i) { o[i][0] *= al0; o[i][1] *= al1; o[i][2] *= al0; o[i][3] *= al1; }
            {
                const uint32_t slot = ring + s3 * (8 * SLOT);
                mbar_wait_warp(fullw + 64 * s3, ph);
#pragma unroll
                for (int mt = 0; mt < 16; ++mt) {
                    uint32_t a[4];
                    ldsm4t(a, slot + (mt >> 2) * 2048 + voff[mt & 3]);
                    mma16816(o[mt], a, pb0, pb1);
                }
                __syncwarp();
                if (lane == 0) mbar_arrive(emptyw + 64 * s3);
                if (++s3 == 3) { s3 = 0; ph ^= 1; }
            }
        }
        uint8_t* red = smem + SM_RED;
        float4* ml = reinterpret_cast<float4*>(smem + SM_ML);
#pragma unroll
        for (int x = 4; x <= 16; x <<= 1) {
            l0 += __shfl_xor_sync(0xffffffffu, l0, x);
            l1 += __shfl_xor_sync(0xffffffffu, l1, x);
        }
        if (t == 0) {
            float2* dst = reinterpret_cast<float2*>(red + w * 2048);
#pragma unroll
            for (int mt = 0; mt < 16; ++mt) {
                dst[mt * 16 + g] = make_float2(o[mt][0], o[mt][1]);
                dst[mt * 16 + 8 + g] = make_float2(o[mt][2], o[mt][3]);
            }
            if (lane == 0) ml[w] = make_float4(m0, m1, l0, l1);
        }
        asm volatile("bar.sync 3, 288;" ::: "memory");
        float4 mw[8];
        float2 rv[8];
#pragma unroll
        for (int i = 0; i < 8; ++i) { mw[i] = ml[i]; rv[i] = reinterpret_cast<const float2*>(red + i * 2048)[tid]; }
        float M0 = mw[0].x, M1 = mw[0].y;
#pragma unroll
        for (int i = 1; i < 8; ++i) { M0 = fmaxf(M0, mw[i].x); M1 = fmaxf(M1, mw[i].y); }
        float O0 = 0.f, O1 = 0.f, L0 = 0.f, L1 = 0.f;
#pragma unroll
        for (int i = 0; i < 8; ++i) {
            const float a0 = ex2(mw[i].x - M0), a1 = ex2(mw[i].y - M1);
            O0 = fmaf(a0, rv[i].x, O0); O1 = fmaf(a1, rv[i].y, O1);
            L0 = fmaf(a0, mw[i].z, L0); L1 = fmaf(a1, mw[i].w, L1);
        }
        uint32_t* rec = scratch + OFF_REC + (tm * 8 + w) * REC_CTA;
        st_pub(rec + r * 32 + lane, encf(O0));
        st_pub(rec + (8 + r) * 32 + lane, encf(O1));
        st_pub_if(lane < 8, rec + 512 + r * 8 + lane, encf(lane == 0 ? M0 : L0));
        st_pub_if(lane < 8, rec + 512 + (8 + r) * 8 + lane, encf(lane == 0 ? M1 : L1));
    }

    uint32_t* const g_p = scratch + OFF_P + tm * 2048;
    uint32_t* const g_ml = scratch + OFF_ML + tm * 256;
    {
        float* const S = reinterpret_cast<float*>(smem + SM_SC) + w * 64;
        uint32_t qf[32];
#pragma unroll
        for (int ks = 0; ks < 16; ++ks) {
            const uint32_t a = qs[(g & 1) * 128 + ks * 8 + t], b = qs[(g & 1) * 128 + ks * 8 + 4 + t];
            qf[2 * ks] = a; qf[2 * ks + 1] = b;
        }
#pragma unroll 1
        for (int it = 0; it < 2; ++it) {
            const uint32_t slot = ring + s3 * (8 * SLOT);
            mbar_wait_warp(fullw + 64 * s3, ph);
            float acc[4][4];
#pragma unroll
            for (int c = 0; c < 4; ++c) { acc[c][0] = 0.f; acc[c][1] = 0.f; acc[c][2] = 0.f; acc[c][3] = 0.f; }
#pragma unroll
            for (int ks = 0; ks < 16; ++ks) {
                uint32_t a[4];
                ldsm4(a, slot + (ks >> 2) * 2048 + koff[ks & 3]);
                mma16816(acc[ks & 3], a, qf[2 * ks], qf[2 * ks + 1]);
            }
            __syncwarp();
            if (lane == 0) mbar_arrive(emptyw + 64 * s3);
            if (++s3 == 3) { s3 = 0; ph ^= 1; }
            const float s0 = (acc[0][0] + acc[1][0]) + (acc[2][0] + acc[3][0]), s1 = (acc[0][1] + acc[1][1]) + (acc[2][1] + acc[3][1]);
            const float s2 = (acc[0][2] + acc[1][2]) + (acc[2][2] + acc[3][2]), s3_ = (acc[0][3] + acc[1][3]) + (acc[2][3] + acc[3][3]);
            const float sv = (t & 2) ? ((t & 1) ? s3_ : s2) : ((t & 1) ? s1 : s0);
            S[(t & 1) * 32 + it * 16 + (t >> 1) * 8 + g] = sv;
        }
        __syncwarp();
        const int hd = (lane >> 2) & 1, tt = lane & 3;
        float2 sv[4];
#pragma unroll
        for (int c = 0; c < 4; ++c) sv[c] = *reinterpret_cast<const float2*>(S + hd * 32 + c * 8 + 2 * tt);
        float mx = fmaxf(fmaxf(fmaxf(sv[0].x, sv[0].y), fmaxf(sv[1].x, sv[1].y)), fmaxf(fmaxf(sv[2].x, sv[2].y), fmaxf(sv[3].x, sv[3].y)));
        mx = fmaxf(mx, __shfl_xor_sync(0xffffffffu, mx, 1));
        mx = fmaxf(mx, __shfl_xor_sync(0xffffffffu, mx, 2));
        const float m = mx * SCALE_LOG2;
        float l = 0.f;
        uint32_t pw[4];
#pragma unroll
        for (int c = 0; c < 4; ++c) {
            const float p0 = ex2(fmaf(sv[c].x, SCALE_LOG2, -m)), p1 = ex2(fmaf(sv[c].y, SCALE_LOG2, -m));
            l += p0 + p1;
            pw[c] = enc(pack_bf16(p0, p1));
        }
        l += __shfl_xor_sync(0xffffffffu, l, 1);
        l += __shfl_xor_sync(0xffffffffu, l, 2);
        st_pub4_if(lane < 8, g_p + (r * 8 + w) * 32 + lane * 4, pw[0], pw[1], pw[2], pw[3]);
        st_pub2_if((lane & 27) == 0, g_ml + (r * 8 + w) * 4 + hd * 2, encf(m), encf(l));
    }

    uint32_t voff[2];
    {
        const int vkey = (lane & 7) + 8 * (lane >> 4), vhi = (lane >> 3) & 1;
#pragma unroll
        for (int c = 0; c < 2; ++c) voff[c] = vkey * 64 + (((2 * c + vhi) ^ ((lane >> 1) & 3)) << 4);
    }
    const int wx = w;
    float fo[4], fv[3];
    __nv_bfloat16* od[3];
    auto project = [&](int seg, uint32_t ow, int grp, uint32_t par) {
        fo[0] = fo[1] = fo[2] = fo[3] = 0.f;
        uint32_t af[4][4];
#pragma unroll
        for (int ks = 0; ks < 4; ++ks) {
            af[ks][0] = __shfl_sync(0xffffffffu, ow, ks * 8 + t);
            af[ks][2] = __shfl_sync(0xffffffffu, ow, ks * 8 + 4 + t);
            af[ks][1] = 0u; af[ks][3] = 0u;
        }
        uint32_t* acc = g_outp + (seg * NACC + (ab * 8 + wx) * 20 + g * 4 + t) * ACC_STRIDE;
        {
            __nv_bfloat16* dst = outp + ab * 896 + seg * 448 + 56 * wx + 2 * t;
#pragma unroll
            for (int k = 0; k < 3; ++k) { const int i = 3 * g + k; od[k] = dst + 8 * (i >> 1) + (i & 1); }
        }
        asm volatile("" : "+l"(acc), "+l"(od[0]), "+l"(od[1]), "+l"(od[2]));
        float c[7][4];
        uint32_t wo[4];
#pragma unroll
        for (int u = 0; u < 4; ++u) {
            const int cc = 7 * wx + 2 * u + (u < 3 ? lane >> 4 : 0);
            wo[u] = sbase + (grp * 8 + ((lane >> 3) & 1)) * SLOT + (lane & 7) * 128 + (cc >> 3) * 1024 + (((cc & 7) ^ (lane & 7)) << 4);
        }
#pragma unroll
        for (int nt = 0; nt < 7; ++nt) c[nt][0] = c[nt][1] = c[nt][2] = c[nt][3] = 0.f;
#pragma unroll
        for (int ks = 0; ks < 4; ++ks) {
            mbar_wait_warp(full0 + 64 * grp + 16 * ks + 8 * (lane & 1), par);
            uint32_t b[3][4], b6[2];
#pragma unroll
            for (int u = 0; u < 3; ++u) ldsm4t(b[u], wo[u] + ks * 2 * SLOT);
            ldsm2t(b6, wo[3] + ks * 2 * SLOT);
#pragma unroll
            for (int u = 0; u < 3; ++u) {
                mma16816(c[2 * u], af[ks], b[u][0], b[u][1]);
                mma16816(c[2 * u + 1], af[ks], b[u][2], b[u][3]);
            }
            mma16816(c[6], af[ks], b6[0], b6[1]);
        }
        float val[15];
#pragma unroll
        for (int nt = 0; nt < 7; ++nt) { val[2 * nt] = c[nt][0]; val[2 * nt + 1] = c[nt][1]; }
        val[14] = 0.f;
        float v0 = val[0], v1 = val[1], v2 = val[2];
#pragma unroll
        for (int k = 1; k < 5; ++k) {
            v0 = g == k ? val[3 * k] : v0; v1 = g == k ? val[3 * k + 1] : v1; v2 = g == k ? val[3 * k + 2] : v2;
        }
        asm volatile("{\n.reg .pred p;\nsetp.ne.u32 p, %9, 0;\n"
                     "@p atom.relaxed.gpu.global.add.v4.f32 {%0,%1,%2,%3}, [%4], {%5,%6,%7,%8};\n}"
                     : "+f"(fo[0]), "+f"(fo[1]), "+f"(fo[2]), "+f"(fo[3])
                     : "l"(acc), "f"(v0), "f"(v1), "f"(v2), "f"(1.0f), "r"((uint32_t)(g < 5)) : "memory");
        fv[0] = v0; fv[1] = v1; fv[2] = v2;
    };
#pragma unroll 1
    for (int seg = 0; seg < 2; ++seg) {
        uint32_t ow;
        if (seg == 0) {
            if (w < 4) {
                const int hh = tid >> 6, dq = (tid >> 3) & 7, sp = tid & 7;
                const uint32_t* myrec = scratch + OFF_REC + (tm * 8 + r) * REC_CTA;
                uint4 v;
                uint2 ml;
                int it = 0;
#pragma unroll 1
                while (true) {
                    v = ld_poll4(myrec + (hh * 8 + sp) * 32 + dq * 4);
                    ml = ld_poll2(myrec + 512 + (hh * 8 + sp) * 8);
                    if (__all_sync(0xffffffffu, v.x && v.y && v.z && v.w && ml.x && ml.y)) break;
                    if (++it > SPIN_LIMIT) __trap();
                }
                st_zero4_if(tid < 16, g_q + ((r >> 2) * 2 + ab) * 2048 + ag * 256 + (r & 3) * 64 + tid * 4);
                const float m = decf(ml.x), l = decf(ml.y);
                float M = m;
#pragma unroll
                for (int x = 1; x <= 4; x <<= 1) M = fmaxf(M, __shfl_xor_sync(0xffffffffu, M, x));
                const float a = ex2(m - M);
                float L = a * l, o0 = a * decf(v.x), o1 = a * decf(v.y), o2 = a * decf(v.z), o3 = a * decf(v.w);
#pragma unroll
                for (int x = 1; x <= 4; x <<= 1) {
                    L += __shfl_xor_sync(0xffffffffu, L, x);
                    o0 += __shfl_xor_sync(0xffffffffu, o0, x);
                    o1 += __shfl_xor_sync(0xffffffffu, o1, x);
                    o2 += __shfl_xor_sync(0xffffffffu, o2, x);
                    o3 += __shfl_xor_sync(0xffffffffu, o3, x);
                }
                const float inv = __frcp_rn(L);
                const uint2 pk = make_uint2(pack_bf16(o0 * inv, o1 * inv), pack_bf16(o2 * inv, o3 * inv));
                if (sp == 0) *reinterpret_cast<uint2*>(smem + SM_OS + hh * 64 + dq * 8) = pk;
            }
            bar_consumers();
            ow = reinterpret_cast<const uint32_t*>(smem + SM_OS)[lane];
        } else {
            const uint32_t* mp = g_ml + lane * 4;
            const uint32_t* pp = g_p + w * 256 + (lane & 7) * 4;
            uint4 a, b, pv[8];
            {
                int it = 0;
#pragma unroll 1
                while (true) {
                    a = ld_poll4(mp);
                    b = ld_poll4(mp + 128);
                    bool ok = true;
#pragma unroll
                    for (int i = 0; i < 8; ++i) pv[i] = ld_poll4(pp + i * 32);
#pragma unroll
                    for (int i = 0; i < 8; ++i) ok = ok && pv[i].x && pv[i].y && pv[i].z && pv[i].w;
                    if (__all_sync(0xffffffffu, ok && a.x && a.y && a.z && a.w && b.x && b.y && b.z && b.w)) break;
                    if (++it > SPIN_LIMIT) __trap();
                }
            }
            float f[8][2];
            {
                const float ma0 = decf(a.x), ma1 = decf(a.z), mb0 = decf(b.x), mb1 = decf(b.z);
                float M0 = fmaxf(ma0, mb0), M1 = fmaxf(ma1, mb1);
#pragma unroll
                for (int x = 1; x <= 16; x <<= 1) {
                    M0 = fmaxf(M0, __shfl_xor_sync(0xffffffffu, M0, x));
                    M1 = fmaxf(M1, __shfl_xor_sync(0xffffffffu, M1, x));
                }
                const float fa0 = ex2(ma0 - M0), fa1 = ex2(ma1 - M1), fb0 = ex2(mb0 - M0), fb1 = ex2(mb1 - M1);
                float L0 = fmaf(fa0, decf(a.y), fb0 * decf(b.y)), L1 = fmaf(fa1, decf(a.w), fb1 * decf(b.w));
#pragma unroll
                for (int x = 1; x <= 16; x <<= 1) {
                    L0 += __shfl_xor_sync(0xffffffffu, L0, x);
                    L1 += __shfl_xor_sync(0xffffffffu, L1, x);
                }
                const float u0 = (w < 4 ? fa0 : fb0) * __frcp_rn(L0), u1 = (w < 4 ? fa1 : fb1) * __frcp_rn(L1);
#pragma unroll
                for (int ks = 0; ks < 8; ++ks) {
                    f[ks][0] = __shfl_sync(0xffffffffu, u0, (w & 3) * 8 + ks);
                    f[ks][1] = __shfl_sync(0xffffffffu, u1, (w & 3) * 8 + ks);
                }
            }
            float acc[8][2][4];
#pragma unroll
            for (int it = 0; it < 2; ++it) {
                const uint32_t slot = ring + s3 * (8 * SLOT);
                mbar_wait_warp(fullw + 64 * s3, ph);
#pragma unroll
                for (int ks = 0; ks < 8; ++ks) {
#pragma unroll
                    for (int mt = 0; mt < 2; ++mt) {
                        uint32_t av[4];
                        ldsm4t(av, slot + ks * 1024 + voff[mt]);
                        if (it == 0) { acc[ks][mt][0] = 0.f; acc[ks][mt][1] = 0.f; acc[ks][mt][2] = 0.f; acc[ks][mt][3] = 0.f; }
                        mma16816(acc[ks][mt], av, ~(it ? pv[ks].z : pv[ks].x), ~(it ? pv[ks].w : pv[ks].y));
                    }
                }
                if (++s3 == 3) { s3 = 0; ph ^= 1; }
            }
            float o[2][4];
#pragma unroll
            for (int mt = 0; mt < 2; ++mt) {
#pragma unroll
                for (int c = 0; c < 4; ++c) {
                    float e = 0.f, d = 0.f;
#pragma unroll
                    for (int ks = 0; ks < 8; ks += 2) { e = fmaf(f[ks][c & 1], acc[ks][mt][c], e); d = fmaf(f[ks + 1][c & 1], acc[ks + 1][mt][c], d); }
                    o[mt][c] = e + d;
                }
            }
            float* const orp = reinterpret_cast<float*>(smem + SM_OR);
            const float v0 = (t & 2) ? ((t & 1) ? o[1][2] : o[1][0]) : ((t & 1) ? o[0][2] : o[0][0]);
            const float v1 = (t & 2) ? ((t & 1) ? o[1][3] : o[1][1]) : ((t & 1) ? o[0][3] : o[0][1]);
            orp[w * 64 + 8 * t + g] = v0;
            orp[w * 64 + 32 + 8 * t + g] = v1;
            bar_consumers();
            float sx = 0.f, sy = 0.f;
#pragma unroll
            for (int i = 0; i < 8; ++i) {
                const float2 v = reinterpret_cast<const float2*>(orp + i * 64)[lane];
                sx += v.x; sy += v.y;
            }
            ow = pack_bf16(sx, sy);
        }
        project(seg, ow, s3, ph);
        if (seg == 0) {
            bar_consumers();
            if (lane == 0) mbar_arrive(emptyw + 64 * s3);
            if (++s3 == 3) { s3 = 0; ph ^= 1; }
        }
        asm volatile("{\n.reg .pred p, q;\n.reg .b16 h0, h1, h2;\n"
                     "setp.eq.f32 p, %0, 0f427C0000;\nsetp.ne.and.u32 q, %7, 0, p;\n"
                     "cvt.rn.bf16.f32 h0, %1;\ncvt.rn.bf16.f32 h1, %2;\ncvt.rn.bf16.f32 h2, %3;\n"
                     "@p st.global.u16 [%4], h0;\n@p st.global.u16 [%5], h1;\n@q st.global.u16 [%6], h2;\n}"
                     ::"f"(fo[3]), "f"(fo[0] + fv[0]), "f"(fo[1] + fv[1]), "f"(fo[2] + fv[2]),
                       "l"(od[0]), "l"(od[1]), "l"(od[2]), "r"((uint32_t)(g < 4)) : "memory");
    }

}

typedef CUresult (*EncodeTiledFn)(CUtensorMap*, CUtensorMapDataType, cuuint32_t, void*, const cuuint64_t*,
                                  const cuuint64_t*, const cuuint32_t*, const cuuint32_t*, CUtensorMapInterleave,
                                  CUtensorMapSwizzle, CUtensorMapL2promotion, CUtensorMapFloatOOBfill);

}

extern "C" void kernel_launch(void* const* d_in, const int* in_sizes, int n_in, void* d_out, int out_size) {
    (void)in_sizes; (void)n_in; (void)out_size;
    static EncodeTiledFn encode = nullptr;
    static uint32_t* scratch = nullptr;
    if (!encode) {
        void* fn = nullptr;
        cudaDriverEntryPointQueryResult qr;
        cudaGetDriverEntryPoint("cuTensorMapEncodeTiled", &fn, cudaEnableDefault, &qr);
        encode = (EncodeTiledFn)fn;
        void* sp = nullptr;
        cudaGetSymbolAddress(&sp, g_scratch);
        scratch = (uint32_t*)sp;
        cudaFuncSetAttribute(fused_decode_kernel, cudaFuncAttributeMaxDynamicSharedMemorySize, SM_TOTAL);
    }
    Maps P;
    for (int p = 0; p < 2; ++p) {
        const cuuint32_t es[3] = {1, 1, 1};
        {
            const cuuint64_t dims[3] = {64, 448, 64};
            const cuuint64_t strides[2] = {8192, 128};
            const cuuint32_t box[3] = {64, 56, 1};
            encode(&P.m[p], CU_TENSOR_MAP_DATA_TYPE_BFLOAT16, 3, d_in[5 * p + 3], dims, strides, box, es,
                   CU_TENSOR_MAP_INTERLEAVE_NONE, CU_TENSOR_MAP_SWIZZLE_NONE, CU_TENSOR_MAP_L2_PROMOTION_NONE,
                   CU_TENSOR_MAP_FLOAT_OOB_FILL_NONE);
        }
        {
            const cuuint64_t dims[3] = {64, 131072, 4};
            const cuuint64_t strides[2] = {512, 128};
            const cuuint32_t box[3] = {64, 16, 4};
            encode(&P.m[2 + 2 * p], CU_TENSOR_MAP_DATA_TYPE_BFLOAT16, 3, d_in[5 * p + 1], dims, strides, box, es,
                   CU_TENSOR_MAP_INTERLEAVE_NONE, CU_TENSOR_MAP_SWIZZLE_128B, CU_TENSOR_MAP_L2_PROMOTION_NONE,
                   CU_TENSOR_MAP_FLOAT_OOB_FILL_NONE);
        }
        if (p == 0) {
            const cuuint64_t dims[3] = {64, 131072, 4};
            const cuuint64_t strides[2] = {512, 128};
            const cuuint32_t box[3] = {64, 16, 4};
            encode(&P.m[3], CU_TENSOR_MAP_DATA_TYPE_BFLOAT16, 3, d_in[2], dims, strides, box, es,
                   CU_TENSOR_MAP_INTERLEAVE_NONE, CU_TENSOR_MAP_SWIZZLE_128B, CU_TENSOR_MAP_L2_PROMOTION_NONE,
                   CU_TENSOR_MAP_FLOAT_OOB_FILL_NONE);
        } else {
            const cuuint64_t dims[3] = {256, 131072, 1};
            const cuuint64_t strides[2] = {512, 512ull * 131072};
            const cuuint32_t box[3] = {32, 128, 1};
            encode(&P.m[5], CU_TENSOR_MAP_DATA_TYPE_BFLOAT16, 3, d_in[7], dims, strides, box, es,
                   CU_TENSOR_MAP_INTERLEAVE_NONE, CU_TENSOR_MAP_SWIZZLE_64B, CU_TENSOR_MAP_L2_PROMOTION_L2_128B,
                   CU_TENSOR_MAP_FLOAT_OOB_FILL_NONE);
        }
        const cuuint64_t dims[3] = {64, 4096, 7};
        const cuuint64_t strides[2] = {896, 128};
        const cuuint32_t box[3] = {64, 8, 7};
        encode(&P.m[6 + p], CU_TENSOR_MAP_DATA_TYPE_BFLOAT16, 3, d_in[5 * p + 4], dims, strides, box, es,
               CU_TENSOR_MAP_INTERLEAVE_NONE, CU_TENSOR_MAP_SWIZZLE_128B, CU_TENSOR_MAP_L2_PROMOTION_NONE,
               CU_TENSOR_MAP_FLOAT_OOB_FILL_NONE);
    }
    fused_decode_kernel<<<NCTA, NTHR, SM_TOTAL, cudaStreamPerThread>>>(d_in[0], d_in[5], scratch, (__nv_bfloat16*)d_out,
                                                                    (const uint8_t*)d_in[1], P);
}
```
